```python
import torch

def _softmax(x, axis=-1):
    return torch.softmax(x, dim=axis)
def _gelu(x):
    return torch.nn.functional.gelu(x, approximate="tanh")
def _silu(x):
    return torch.nn.functional.silu(x)
def _sigmoid(x):
    return torch.sigmoid(x)
def _layernorm(x, axis=-1, eps=1e-5):
    m = x.mean(dim=axis, keepdim=True)
    v = x.var(dim=axis, keepdim=True, unbiased=False)
    return (x - m) / torch.sqrt(v + eps)
def _scatter_add(tgt, idx, src, axis=0):
    return tgt.clone().index_add_(axis, idx, src)
def _segment_sum(src, seg, n):
    out = torch.zeros((n,) + src.shape[1:], dtype=src.dtype)
    return out.index_add_(0, seg, src)
def _pad(x, pw):
    flat = tuple(v for pair in reversed(pw) for v in pair)
    return torch.nn.functional.pad(x, flat)

kernel_name = 'gated_mix__sliding_local_dilated__dense_activation_mish__prompt'

def setup_inputs():

    _w = (lambda a: (lambda t: t.to(torch.bfloat16) if t.is_floating_point() else t)(torch.as_tensor(a)))
    def _A_setup():
        B, S, D = 1, 2048, 640
        return {
            "x": _w((lambda *s: torch.randn(*s, dtype=torch.bfloat16) * 0.05)(B, S, D)),
            "wqkv": _w((lambda *s: torch.randn(*s, dtype=torch.bfloat16) * 0.8)(D, 3 * D)),
            "wo": _w((lambda *s: torch.randn(*s, dtype=torch.bfloat16) * 0.05)(D, D)),
        }
    _A_in = _A_setup()

    def _B_setup():
        B, S, D, F = 1, 2048, 640, 1728
        return {
            "x": _w((lambda *s: torch.randn(*s, dtype=torch.bfloat16) * 0.05)(B, S, D)),
            "w1": _w((lambda *s: torch.randn(*s, dtype=torch.bfloat16) * 12.8)(D, F) * (D ** -0.5)),
            "b1": _w((lambda *s: torch.randn(*s, dtype=torch.bfloat16) * 0.8)(F)),
            "w2": _w((lambda *s: torch.randn(*s, dtype=torch.bfloat16) * 0.8)(F, D) * (F ** -0.5)),
        }
    _B_in = _B_setup()

    return {
        "A_x": _A_in["x"],
        "A_wqkv": _A_in["wqkv"],
        "A_wo": _A_in["wo"],
        "B_x": _B_in["x"],
        "B_w1": _B_in["w1"],
        "B_b1": _B_in["b1"],
        "B_w2": _B_in["w2"],
        "gate_w": _w((lambda *s: torch.randn(*s, dtype=torch.bfloat16) * 0.05)(640) * 16.0),
    }

def reference(A_x, A_wqkv, A_wo, B_x, B_w1, B_b1, B_w2, gate_w):
    def _A_ref(x, wqkv, wo):
        B, S, D = x.shape
        H = 32; Dh = D // H
        W, dil = 8, 2
        qkv = (lambda x, *d: x.permute(*d))((x @ wqkv).reshape(B, S, 3, H, Dh), 2, 0, 3, 1, 4)
        q, k, v = qkv[0], qkv[1], qkv[2]
        scale = Dh ** -0.5
        pos = torch.arange(S)
        off = torch.arange(W) * dil
        idx = pos[:, None] - off[None, :]
        mask = idx >= 0
        idx_c = torch.where(mask, idx, 0).reshape(-1)
        kg = k[:, :, idx_c, :].reshape(B, H, S, W, Dh)
        vg = v[:, :, idx_c, :].reshape(B, H, S, W, Dh)
        logits = torch.einsum("bhsd,bhswd->bhsw", q, kg) * scale
        logits = torch.where(mask[None, None, :, :], logits, -1e9)
        attn = _softmax(logits, axis=-1)
        o = torch.einsum("bhsw,bhswd->bhsd", attn, vg)
        return (lambda x, *d: x.permute(*d))(o, 0, 2, 1, 3).reshape(B, S, D) @ wo

    def _B_ref(x, w1, b1, w2):
        h = torch.einsum("bsd,df->bsf", x, w1) + b1
        sp = torch.log1p(torch.exp(-torch.abs(h))) + torch.where(h > 0, h, torch.zeros_like(h))
        act = h * torch.tanh(sp)
        return torch.einsum("bsf,fd->bsd", act, w2)

    x = A_x
    g = _sigmoid((x * gate_w).sum(-1, keepdims=True))
    a = _A_ref(x, A_wqkv, A_wo)
    b = _B_ref(x, B_w1, B_b1, B_w2)
    return g * a + (1 - g) * b
```

```cpp
#include <cuda_runtime.h>
#include <cuda.h>
#include <cuda_bf16.h>
#include <stdint.h>

namespace {

constexpr int SEQ = 2048, DM = 640, FF = 1728, QKVN = 1920;
constexpr int NTHREADS = 384;
constexpr int NREG_CTAS = 128;
constexpr int NCTAS = 132;

constexpr int RING_BYTES = 163840;
constexpr int SLOT1 = 49152;
constexpr int SLOT2 = 40960;
constexpr int STG_OFF = RING_BYTES;
constexpr int STG_BYTES = 66048;
constexpr int ATT_K_OFF = 20480;
constexpr int ATT_V_OFF = 43264;
constexpr int MISC_OFF = STG_OFF + STG_BYTES;
constexpr int SG_OFF = MISC_OFF + 256;
constexpr int SMEM_USED = SG_OFF + 512;
constexpr int SMEM_ALLOC = SMEM_USED + 1024;

enum { B_FULLA = 0, B_EMPTYA = 3, B_FULLB = 6, B_EMPTYB = 9, B_FULLC = 12, B_EMPTYC = 16,
       B_STGFULL = 20, B_STGEMPTY = 21, B_ATTFULL = 22, B_PEERFREE = 23, B_PEERDATA = 24, B_COUNT = 25 };

enum { F_H = 0, F_QKV = 16, F_O = 32, F_FIN = 48 };

__device__ __nv_bfloat16 g_h[SEQ * FF];
__device__ __nv_bfloat16 g_o[SEQ * DM];
__device__ __nv_bfloat16 g_qkv[SEQ * QKVN];
__device__ unsigned g_flags[64];

struct Maps { CUtensorMap x, wqkv, w1, w2, wo, h, o, qkv_st, qkv_ldq, qkv_ldkv; };

__device__ __forceinline__ uint32_t s2u(const void* p) { return (uint32_t)__cvta_generic_to_shared(p); }
__device__ __forceinline__ void mbar_init(uint32_t b, int c) { asm volatile("mbarrier.init.shared::cta.b64 [%0], %1;" ::"r"(b), "r"(c)); }
__device__ __forceinline__ void mbar_expect(uint32_t b, int bytes) { asm volatile("mbarrier.arrive.expect_tx.shared::cta.b64 _, [%0], %1;" ::"r"(b), "r"(bytes) : "memory"); }
__device__ __forceinline__ void mbar_arrive(uint32_t b) { asm volatile("mbarrier.arrive.shared::cta.b64 _, [%0];" ::"r"(b) : "memory"); }
__device__ __forceinline__ bool mbar_try(uint32_t b, int par) {
  uint32_t ok;
  asm volatile("{\n.reg .pred p;\nmbarrier.try_wait.parity.shared::cta.b64 p, [%1], %2;\nselp.u32 %0, 1, 0, p;\n}" : "=r"(ok) : "r"(b), "r"(par) : "memory");
  return ok != 0;
}
#define TRAP(c, e) __trap()
__device__ __forceinline__ void mbar_wait(uint32_t b, int par) {
  uint32_t n = 0;
  while (!mbar_try(b, par)) { if (++n > (1u << 22)) TRAP(1, (b & 255) / 8 + 1000 * par); }
}
__device__ __forceinline__ bool mbar_try_cl(uint32_t b, int par) {
  uint32_t ok;
  asm volatile("{\n.reg .pred p;\nmbarrier.try_wait.parity.acquire.cluster.shared::cta.b64 p, [%1], %2;\nselp.u32 %0, 1, 0, p;\n}" : "=r"(ok) : "r"(b), "r"(par) : "memory");
  return ok != 0;
}
__device__ __forceinline__ void mbar_wait_cl(uint32_t b, int par) {
  uint32_t n = 0;
  while (!mbar_try_cl(b, par)) { if (++n > (1u << 22)) TRAP(2, (b & 255) / 8); }
}
__device__ __forceinline__ uint32_t mapa(uint32_t a, uint32_t cta) { uint32_t r; asm volatile("mapa.shared::cluster.u32 %0, %1, %2;" : "=r"(r) : "r"(a), "r"(cta)); return r; }
__device__ __forceinline__ void mbar_arrive_cl(uint32_t remote) { asm volatile("mbarrier.arrive.release.cluster.shared::cluster.b64 _, [%0];" ::"r"(remote) : "memory"); }
__device__ __forceinline__ void tma_load(uint32_t dst, const CUtensorMap* m, uint32_t bar, int c0, int c1) {
  asm volatile("cp.async.bulk.tensor.2d.shared::cluster.global.mbarrier::complete_tx::bytes [%0], [%1, {%3,%4}], [%2];" ::"r"(dst), "l"(m), "r"(bar), "r"(c0), "r"(c1) : "memory");
}
__device__ __forceinline__ void tma_store(const CUtensorMap* m, uint32_t src, int c0, int c1) {
  asm volatile("cp.async.bulk.tensor.2d.global.shared::cta.bulk_group [%0, {%2,%3}], [%1];" ::"l"(m), "r"(src), "r"(c0), "r"(c1) : "memory");
}
__device__ __forceinline__ void fence_async() { asm volatile("fence.proxy.async;" ::: "memory"); }
__device__ __forceinline__ void wg_fence() { asm volatile("wgmma.fence.sync.aligned;" ::: "memory"); }
__device__ __forceinline__ void wg_commit() { asm volatile("wgmma.commit_group.sync.aligned;" ::: "memory"); }
template <int N> __device__ __forceinline__ void wg_wait() { asm volatile("wgmma.wait_group.sync.aligned %0;" ::"n"(N) : "memory"); }
__device__ __forceinline__ void named_bar(int id, int n) { asm volatile("bar.sync %0, %1;" ::"r"(id), "r"(n) : "memory"); }
__device__ __forceinline__ unsigned ld_acq(const unsigned* p) { unsigned v; asm volatile("ld.acquire.gpu.global.u32 %0, [%1];" : "=r"(v) : "l"(p) : "memory"); return v; }
__device__ __forceinline__ void flag_add(unsigned* p) { asm volatile("red.release.gpu.global.add.u32 [%0], 1;" ::"l"(p) : "memory"); }
__device__ __forceinline__ void flag_wait(const unsigned* p, unsigned target) {
  uint32_t n = 0;
  while (ld_acq(p) < target) { __nanosleep(40); if (++n > (1u << 20)) TRAP(3, (unsigned)(p - g_flags)); }
}
__device__ __forceinline__ void finish_reader() {
  unsigned old = atomicAdd(&g_flags[F_FIN], 1u);
  if (old == 2 * NREG_CTAS - 1) {
    for (int i = 0; i <= F_FIN; i++) g_flags[i] = 0;
    __threadfence();
  }
}
__device__ __forceinline__ uint32_t pack_bf16(float a, float b) { __nv_bfloat162 t = __floats2bfloat162_rn(a, b); return *reinterpret_cast<uint32_t*>(&t); }
__device__ __forceinline__ float bf_lo(uint32_t v) { return __uint_as_float(v << 16); }
__device__ __forceinline__ float bf_hi(uint32_t v) { return __uint_as_float(v & 0xffff0000u); }

__device__ __forceinline__ uint64_t desc_a(uint32_t a) { return (uint64_t)((a & 0x3FFFF) >> 4) | (1ull << 16) | (64ull << 32) | (1ull << 62); }
__device__ __forceinline__ uint64_t desc_b(uint32_t a) { return (uint64_t)((a & 0x3FFFF) >> 4) | (512ull << 16) | (64ull << 32) | (1ull << 62); }

__device__ __forceinline__ void wgmma_n256(float (&d)[128], uint64_t da, uint64_t db, int sc) {
  asm volatile("{\n.reg .pred p;\nsetp.ne.b32 p, %130, 0;\n"
    "wgmma.mma_async.sync.aligned.m64n256k16.f32.bf16.bf16 {%0, %1, %2, %3, %4, %5, %6, %7, %8, %9, %10, %11, %12, %13, %14, %15, %16, %17, %18, %19, %20, %21, %22, %23, %24, %25, %26, %27, %28, %29, %30, %31, %32, %33, %34, %35, %36, %37, %38, %39, %40, %41, %42, %43, %44, %45, %46, %47, %48, %49, %50, %51, %52, %53, %54, %55, %56, %57, %58, %59, %60, %61, %62, %63, %64, %65, %66, %67, %68, %69, %70, %71, %72, %73, %74, %75, %76, %77, %78, %79, %80, %81, %82, %83, %84, %85, %86, %87, %88, %89, %90, %91, %92, %93, %94, %95, %96, %97, %98, %99, %100, %101, %102, %103, %104, %105, %106, %107, %108, %109, %110, %111, %112, %113, %114, %115, %116, %117, %118, %119, %120, %121, %122, %123, %124, %125, %126, %127}, %128, %129, p, 1, 1, 0, 1;\n}\n"
    : "+f"(d[0]), "+f"(d[1]), "+f"(d[2]), "+f"(d[3]), "+f"(d[4]), "+f"(d[5]), "+f"(d[6]), "+f"(d[7]), "+f"(d[8]), "+f"(d[9]), "+f"(d[10]), "+f"(d[11]), "+f"(d[12]), "+f"(d[13]), "+f"(d[14]), "+f"(d[15]), "+f"(d[16]), "+f"(d[17]), "+f"(d[18]), "+f"(d[19]), "+f"(d[20]), "+f"(d[21]), "+f"(d[22]), "+f"(d[23]), "+f"(d[24]), "+f"(d[25]), "+f"(d[26]), "+f"(d[27]), "+f"(d[28]), "+f"(d[29]), "+f"(d[30]), "+f"(d[31]), "+f"(d[32]), "+f"(d[33]), "+f"(d[34]), "+f"(d[35]), "+f"(d[36]), "+f"(d[37]), "+f"(d[38]), "+f"(d[39]), "+f"(d[40]), "+f"(d[41]), "+f"(d[42]), "+f"(d[43]), "+f"(d[44]), "+f"(d[45]), "+f"(d[46]), "+f"(d[47]), "+f"(d[48]), "+f"(d[49]), "+f"(d[50]), "+f"(d[51]), "+f"(d[52]), "+f"(d[53]), "+f"(d[54]), "+f"(d[55]), "+f"(d[56]), "+f"(d[57]), "+f"(d[58]), "+f"(d[59]), "+f"(d[60]), "+f"(d[61]), "+f"(d[62]), "+f"(d[63]), "+f"(d[64]), "+f"(d[65]), "+f"(d[66]), "+f"(d[67]), "+f"(d[68]), "+f"(d[69]), "+f"(d[70]), "+f"(d[71]), "+f"(d[72]), "+f"(d[73]), "+f"(d[74]), "+f"(d[75]), "+f"(d[76]), "+f"(d[77]), "+f"(d[78]), "+f"(d[79]), "+f"(d[80]), "+f"(d[81]), "+f"(d[82]), "+f"(d[83]), "+f"(d[84]), "+f"(d[85]), "+f"(d[86]), "+f"(d[87]), "+f"(d[88]), "+f"(d[89]), "+f"(d[90]), "+f"(d[91]), "+f"(d[92]), "+f"(d[93]), "+f"(d[94]), "+f"(d[95]), "+f"(d[96]), "+f"(d[97]), "+f"(d[98]), "+f"(d[99]), "+f"(d[100]), "+f"(d[101]), "+f"(d[102]), "+f"(d[103]), "+f"(d[104]), "+f"(d[105]), "+f"(d[106]), "+f"(d[107]), "+f"(d[108]), "+f"(d[109]), "+f"(d[110]), "+f"(d[111]), "+f"(d[112]), "+f"(d[113]), "+f"(d[114]), "+f"(d[115]), "+f"(d[116]), "+f"(d[117]), "+f"(d[118]), "+f"(d[119]), "+f"(d[120]), "+f"(d[121]), "+f"(d[122]), "+f"(d[123]), "+f"(d[124]), "+f"(d[125]), "+f"(d[126]), "+f"(d[127])
    : "l"(da), "l"(db), "r"(sc));
}
__device__ __forceinline__ void wgmma_n192(float (&d)[96], uint64_t da, uint64_t db, int sc) {
  asm volatile("{\n.reg .pred p;\nsetp.ne.b32 p, %98, 0;\n"
    "wgmma.mma_async.sync.aligned.m64n192k16.f32.bf16.bf16 {%0, %1, %2, %3, %4, %5, %6, %7, %8, %9, %10, %11, %12, %13, %14, %15, %16, %17, %18, %19, %20, %21, %22, %23, %24, %25, %26, %27, %28, %29, %30, %31, %32, %33, %34, %35, %36, %37, %38, %39, %40, %41, %42, %43, %44, %45, %46, %47, %48, %49, %50, %51, %52, %53, %54, %55, %56, %57, %58, %59, %60, %61, %62, %63, %64, %65, %66, %67, %68, %69, %70, %71, %72, %73, %74, %75, %76, %77, %78, %79, %80, %81, %82, %83, %84, %85, %86, %87, %88, %89, %90, %91, %92, %93, %94, %95}, %96, %97, p, 1, 1, 0, 1;\n}\n"
    : "+f"(d[0]), "+f"(d[1]), "+f"(d[2]), "+f"(d[3]), "+f"(d[4]), "+f"(d[5]), "+f"(d[6]), "+f"(d[7]), "+f"(d[8]), "+f"(d[9]), "+f"(d[10]), "+f"(d[11]), "+f"(d[12]), "+f"(d[13]), "+f"(d[14]), "+f"(d[15]), "+f"(d[16]), "+f"(d[17]), "+f"(d[18]), "+f"(d[19]), "+f"(d[20]), "+f"(d[21]), "+f"(d[22]), "+f"(d[23]), "+f"(d[24]), "+f"(d[25]), "+f"(d[26]), "+f"(d[27]), "+f"(d[28]), "+f"(d[29]), "+f"(d[30]), "+f"(d[31]), "+f"(d[32]), "+f"(d[33]), "+f"(d[34]), "+f"(d[35]), "+f"(d[36]), "+f"(d[37]), "+f"(d[38]), "+f"(d[39]), "+f"(d[40]), "+f"(d[41]), "+f"(d[42]), "+f"(d[43]), "+f"(d[44]), "+f"(d[45]), "+f"(d[46]), "+f"(d[47]), "+f"(d[48]), "+f"(d[49]), "+f"(d[50]), "+f"(d[51]), "+f"(d[52]), "+f"(d[53]), "+f"(d[54]), "+f"(d[55]), "+f"(d[56]), "+f"(d[57]), "+f"(d[58]), "+f"(d[59]), "+f"(d[60]), "+f"(d[61]), "+f"(d[62]), "+f"(d[63]), "+f"(d[64]), "+f"(d[65]), "+f"(d[66]), "+f"(d[67]), "+f"(d[68]), "+f"(d[69]), "+f"(d[70]), "+f"(d[71]), "+f"(d[72]), "+f"(d[73]), "+f"(d[74]), "+f"(d[75]), "+f"(d[76]), "+f"(d[77]), "+f"(d[78]), "+f"(d[79]), "+f"(d[80]), "+f"(d[81]), "+f"(d[82]), "+f"(d[83]), "+f"(d[84]), "+f"(d[85]), "+f"(d[86]), "+f"(d[87]), "+f"(d[88]), "+f"(d[89]), "+f"(d[90]), "+f"(d[91]), "+f"(d[92]), "+f"(d[93]), "+f"(d[94]), "+f"(d[95])
    : "l"(da), "l"(db), "r"(sc));
}
__device__ __forceinline__ void wgmma_n160(float (&d)[80], uint64_t da, uint64_t db, int sc) {
  asm volatile("{\n.reg .pred p;\nsetp.ne.b32 p, %82, 0;\n"
    "wgmma.mma_async.sync.aligned.m64n160k16.f32.bf16.bf16 {%0, %1, %2, %3, %4, %5, %6, %7, %8, %9, %10, %11, %12, %13, %14, %15, %16, %17, %18, %19, %20, %21, %22, %23, %24, %25, %26, %27, %28, %29, %30, %31, %32, %33, %34, %35, %36, %37, %38, %39, %40, %41, %42, %43, %44, %45, %46, %47, %48, %49, %50, %51, %52, %53, %54, %55, %56, %57, %58, %59, %60, %61, %62, %63, %64, %65, %66, %67, %68, %69, %70, %71, %72, %73, %74, %75, %76, %77, %78, %79}, %80, %81, p, 1, 1, 0, 1;\n}\n"
    : "+f"(d[0]), "+f"(d[1]), "+f"(d[2]), "+f"(d[3]), "+f"(d[4]), "+f"(d[5]), "+f"(d[6]), "+f"(d[7]), "+f"(d[8]), "+f"(d[9]), "+f"(d[10]), "+f"(d[11]), "+f"(d[12]), "+f"(d[13]), "+f"(d[14]), "+f"(d[15]), "+f"(d[16]), "+f"(d[17]), "+f"(d[18]), "+f"(d[19]), "+f"(d[20]), "+f"(d[21]), "+f"(d[22]), "+f"(d[23]), "+f"(d[24]), "+f"(d[25]), "+f"(d[26]), "+f"(d[27]), "+f"(d[28]), "+f"(d[29]), "+f"(d[30]), "+f"(d[31]), "+f"(d[32]), "+f"(d[33]), "+f"(d[34]), "+f"(d[35]), "+f"(d[36]), "+f"(d[37]), "+f"(d[38]), "+f"(d[39]), "+f"(d[40]), "+f"(d[41]), "+f"(d[42]), "+f"(d[43]), "+f"(d[44]), "+f"(d[45]), "+f"(d[46]), "+f"(d[47]), "+f"(d[48]), "+f"(d[49]), "+f"(d[50]), "+f"(d[51]), "+f"(d[52]), "+f"(d[53]), "+f"(d[54]), "+f"(d[55]), "+f"(d[56]), "+f"(d[57]), "+f"(d[58]), "+f"(d[59]), "+f"(d[60]), "+f"(d[61]), "+f"(d[62]), "+f"(d[63]), "+f"(d[64]), "+f"(d[65]), "+f"(d[66]), "+f"(d[67]), "+f"(d[68]), "+f"(d[69]), "+f"(d[70]), "+f"(d[71]), "+f"(d[72]), "+f"(d[73]), "+f"(d[74]), "+f"(d[75]), "+f"(d[76]), "+f"(d[77]), "+f"(d[78]), "+f"(d[79])
    : "l"(da), "l"(db), "r"(sc));
}
__device__ __forceinline__ void wgmma_n64(float (&d)[32], uint64_t da, uint64_t db, int sc) {
  asm volatile("{\n.reg .pred p;\nsetp.ne.b32 p, %34, 0;\n"
    "wgmma.mma_async.sync.aligned.m64n64k16.f32.bf16.bf16 {%0, %1, %2, %3, %4, %5, %6, %7, %8, %9, %10, %11, %12, %13, %14, %15, %16, %17, %18, %19, %20, %21, %22, %23, %24, %25, %26, %27, %28, %29, %30, %31}, %32, %33, p, 1, 1, 0, 1;\n}\n"
    : "+f"(d[0]), "+f"(d[1]), "+f"(d[2]), "+f"(d[3]), "+f"(d[4]), "+f"(d[5]), "+f"(d[6]), "+f"(d[7]), "+f"(d[8]), "+f"(d[9]), "+f"(d[10]), "+f"(d[11]), "+f"(d[12]), "+f"(d[13]), "+f"(d[14]), "+f"(d[15]), "+f"(d[16]), "+f"(d[17]), "+f"(d[18]), "+f"(d[19]), "+f"(d[20]), "+f"(d[21]), "+f"(d[22]), "+f"(d[23]), "+f"(d[24]), "+f"(d[25]), "+f"(d[26]), "+f"(d[27]), "+f"(d[28]), "+f"(d[29]), "+f"(d[30]), "+f"(d[31])
    : "l"(da), "l"(db), "r"(sc));
}

template <int N> struct MMA;
template <> struct MMA<256> { static __device__ __forceinline__ void run(float (&d)[128], uint64_t a, uint64_t b, int s) { wgmma_n256(d, a, b, s); } };
template <> struct MMA<192> { static __device__ __forceinline__ void run(float (&d)[96], uint64_t a, uint64_t b, int s) { wgmma_n192(d, a, b, s); } };
template <> struct MMA<160> { static __device__ __forceinline__ void run(float (&d)[80], uint64_t a, uint64_t b, int s) { wgmma_n160(d, a, b, s); } };
template <> struct MMA<64>  { static __device__ __forceinline__ void run(float (&d)[32], uint64_t a, uint64_t b, int s) { wgmma_n64(d, a, b, s); } };

template <int N, int NS, int SLOTB>
__device__ __forceinline__ void mainloop(float (&acc)[N / 2], uint32_t ring, uint32_t fullb, uint32_t emptyb,
                                         int& slot, int& cnt, int nk, int wg, int lane) {
  int prev = -1;
#pragma unroll
  for (int i = 0; i < N / 2; i++) acc[i] = 0.f;
  for (int k = 0; k < nk; k++) {
    mbar_wait(fullb + slot * 8, (cnt / NS) & 1);
    uint32_t base = ring + slot * SLOTB;
    uint64_t da = desc_a(base + wg * 8192);
    uint64_t db = desc_b(base + 16384);
    wg_fence();
#pragma unroll
    for (int kk = 0; kk < 4; kk++) MMA<N>::run(acc, da + kk * 2, db + kk * 128, 1);
    wg_commit();
    wg_wait<1>();
    if (prev >= 0 && lane == 0) mbar_arrive(emptyb + prev * 8);
    prev = slot;
    cnt++;
    if (++slot == NS) slot = 0;
  }
  wg_wait<0>();
  if (lane == 0) mbar_arrive(emptyb + prev * 8);
#pragma unroll
  for (int i = 0; i < N / 2; i++) asm volatile("" : "+f"(acc[i])::"memory");
}

template <int N>
__device__ __forceinline__ void dump_tile(float (&acc)[N / 2], uint32_t stg, int wg, int warp, int lane) {
  int row = wg * 64 + warp * 16 + (lane & 7) + ((lane >> 3) & 1) * 8;
  uint32_t rbase = stg + row * 128;
  int csel = lane >> 4;
#pragma unroll
  for (int jb = 0; jb < N / 8; jb += 2) {
    uint32_t r0 = pack_bf16(acc[4 * jb + 0], acc[4 * jb + 1]);
    uint32_t r1 = pack_bf16(acc[4 * jb + 2], acc[4 * jb + 3]);
    uint32_t r2 = pack_bf16(acc[4 * jb + 4], acc[4 * jb + 5]);
    uint32_t r3 = pack_bf16(acc[4 * jb + 6], acc[4 * jb + 7]);
    int cb = jb + csel;
    uint32_t addr = rbase + (cb >> 3) * 16384 + (((cb & 7) ^ (row & 7)) << 4);
    asm volatile("stmatrix.sync.aligned.m8n8.x4.shared.b16 [%0], {%1,%2,%3,%4};" ::"r"(addr), "r"(r0), "r"(r1), "r"(r2), "r"(r3) : "memory");
  }
}

template <int N>
__device__ __forceinline__ void phase1_tile(uint32_t ring, uint32_t bars, uint32_t fullb, uint32_t emptyb, int& slot, int& cnt,
                                            int stg_use, int wg, int warp, int lane) {
  float acc[N / 2];
  mainloop<N, 3, SLOT1>(acc, ring, fullb, emptyb, slot, cnt, 10, wg, lane);
  mbar_wait(bars + B_STGEMPTY * 8, (stg_use & 1) ^ 1);
  dump_tile<N>(acc, ring + STG_OFF, wg, warp, lane);
  fence_async();
  __syncwarp();
  if (lane == 0) mbar_arrive(bars + B_STGFULL * 8);
}

__device__ __forceinline__ float mish_f(float x) {
  float e = __expf(fminf(x, 20.f));
  float n = e * (e + 2.f);
  return x * __fdividef(n, n + 2.f);
}

__device__ __forceinline__ void load_row20(uint32_t addr, float (&f)[20]) {
#pragma unroll
  for (int i = 0; i < 5; i++) {
    uint32_t a, b;
    asm volatile("ld.shared.v2.u32 {%0,%1}, [%2];" : "=r"(a), "=r"(b) : "r"(addr + i * 8));
    f[4 * i + 0] = bf_lo(a); f[4 * i + 1] = bf_hi(a); f[4 * i + 2] = bf_lo(b); f[4 * i + 3] = bf_hi(b);
  }
}

__global__ void __cluster_dims__(2, 1, 1) __launch_bounds__(NTHREADS, 1)
fused_kernel(const __grid_constant__ Maps maps, const __nv_bfloat16* __restrict__ b1,
             const __nv_bfloat16* __restrict__ gate_w, __nv_bfloat16* __restrict__ out) {
  extern __shared__ uint8_t smem_raw[];
  const uint32_t ring = (s2u(smem_raw) + 1023) & ~1023u;
  const uint32_t bars = ring + MISC_OFF;
  const int tid = threadIdx.x, wgi = tid >> 7, warp = (tid >> 5) & 3, lane = tid & 31;
  const int cta = blockIdx.x;
  const bool regular = cta < NREG_CTAS;
  const int rb = cta & 15, j = cta >> 4;
  const int ntilesA = regular ? 1 : 4;
  const int w1_at0 = regular ? (j < 6 ? 3 * j : 18 + 4 * (j - 6)) : 26;
  const int w1_nat = regular ? (j < 6 ? 3 : 4) : 1;
  const int qkv_at0 = j < 6 ? 4 * j : 24 + 3 * (j - 6);
  const int qkv_nat = j < 6 ? 4 : 3;
  const int rank = cta & 1, pr = cta >> 1;
  const int rb2 = pr & 15, nt = pr >> 4;

  if (tid == 0) {
    for (int i = 0; i < 3; i++) { mbar_init(bars + (B_FULLA + i) * 8, 1); mbar_init(bars + (B_EMPTYA + i) * 8, 11);
                                  mbar_init(bars + (B_FULLB + i) * 8, 1); mbar_init(bars + (B_EMPTYB + i) * 8, 8); }
    for (int i = 0; i < 4; i++) { mbar_init(bars + (B_FULLC + i) * 8, 1); mbar_init(bars + (B_EMPTYC + i) * 8, 8); }
    mbar_init(bars + B_STGFULL * 8, 8);
    mbar_init(bars + B_STGEMPTY * 8, 3);
    mbar_init(bars + B_ATTFULL * 8, 1);
    mbar_init(bars + B_PEERFREE * 8, 8);
    mbar_init(bars + B_PEERDATA * 8, 256);
    asm volatile("fence.mbarrier_init.release.cluster;" ::: "memory");
  }
  asm volatile("barrier.cluster.arrive.release.aligned;\nbarrier.cluster.wait.acquire.aligned;" ::: "memory");

  if (wgi == 0) {
   asm volatile("setmaxnreg.dec.sync.aligned.u32 104;");
   if (tid < 32) {
    if (tid == 0) {
      int slot = 0, cnt = 0;
      for (int t = 0; t < ntilesA; t++) {
        int rbt = regular ? rb : (cta - NREG_CTAS) * 4 + t;
        for (int k = 0; k < 10; k++) {
          mbar_wait(bars + (B_EMPTYA + slot) * 8, ((cnt / 3) & 1) ^ 1);
          uint32_t base = ring + slot * SLOT1, fb = bars + (B_FULLA + slot) * 8;
          mbar_expect(fb, 16384 + w1_nat * 8192);
          tma_load(base, &maps.x, fb, k * 64, rbt * 128);
          for (int a = 0; a < w1_nat; a++) tma_load(base + 16384 + a * 8192, &maps.w1, fb, (w1_at0 + a) * 64, k * 64);
          cnt++; if (++slot == 3) slot = 0;
        }
      }
      if (regular) {
        for (int k = 0; k < 10; k++) {
          if (k < 3) mbar_wait(bars + (B_EMPTYA + slot) * 8, slot == 0 ? 1 : 0);
          else mbar_wait(bars + (B_EMPTYB + slot) * 8, ((k / 3) & 1) ^ 1);
          uint32_t base = ring + slot * SLOT1, fb = bars + (B_FULLB + slot) * 8;
          mbar_expect(fb, 16384 + qkv_nat * 8192);
          tma_load(base, &maps.x, fb, k * 64, rb * 128);
          for (int a = 0; a < qkv_nat; a++) tma_load(base + 16384 + a * 8192, &maps.wqkv, fb, (qkv_at0 + a) * 64, k * 64);
          if (++slot == 3) slot = 0;
        }
        const int nh = rank == 0 ? 14 : 13, h0 = rank == 0 ? 0 : 14, o0 = rank == 0 ? 0 : 5;
        const int c0 = (nt & 1) ? 160 * nt + 32 : 160 * nt;
        const int c2 = (nt & 1) ? 160 * nt : 160 * nt + 128;
        flag_wait(&g_flags[F_H + rb2], 9);
        fence_async();
        slot = 3;
        for (int i = 0; i < nh + 5; i++) {
          if (i < 4) {
            if (slot == 3) mbar_wait(bars + (B_EMPTYB + 2) * 8, 0);
            else if (slot == 0) mbar_wait(bars + (B_EMPTYB + 0) * 8, 0);
            else mbar_wait(bars + (B_EMPTYB + 1) * 8, 1);
          } else mbar_wait(bars + (B_EMPTYC + slot) * 8, ((i >> 2) & 1) ^ 1);
          if (i == nh) { flag_wait(&g_flags[F_O + rb2], 8); fence_async(); }
          uint32_t base = ring + slot * SLOT2, fb = bars + (B_FULLC + slot) * 8;
          mbar_expect(fb, 16384 + 3 * 8192);
          const bool hp = i < nh;
          const int kc = (hp ? h0 + i : o0 + i - nh) * 64;
          const CUtensorMap* ma = hp ? &maps.h : &maps.o;
          const CUtensorMap* mb = hp ? &maps.w2 : &maps.wo;
          tma_load(base, ma, fb, kc, rb2 * 128);
          tma_load(base + 16384, mb, fb, c0, kc);
          tma_load(base + 16384 + 8192, mb, fb, c0 + 64, kc);
          tma_load(base + 16384 + 16384, mb, fb, c2, kc);
          slot = (slot + 1) & 3;
        }
        finish_reader();
      }
    }
   } else {
    const int t = tid - 32;
    const uint32_t stg = ring + STG_OFF;
    const uint32_t sG = ring + SG_OFF;
    int slot = 0, cnt = 0;
    for (int tl = 0; tl < ntilesA; tl++) {
      int rbt = regular ? rb : (cta - NREG_CTAS) * 4 + tl;
      float dot = 0.f, dot2 = 0.f;
      for (int k = 0; k < 10; k++) {
        mbar_wait(bars + (B_FULLA + slot) * 8, (cnt / 3) & 1);
        uint32_t rbase = ring + slot * SLOT1 + t * 128;
#pragma unroll
        for (int c = 0; c < 8; c++) {
          uint32_t a0, a1, a2, a3;
          asm volatile("ld.shared.v4.u32 {%0,%1,%2,%3}, [%4];" : "=r"(a0), "=r"(a1), "=r"(a2), "=r"(a3) : "r"(rbase + ((c ^ (t & 7)) << 4)));
          uint4 w = __ldg(reinterpret_cast<const uint4*>(gate_w + k * 64 + c * 8));
          dot += bf_lo(a0) * bf_lo(w.x) + bf_hi(a0) * bf_hi(w.x) + bf_lo(a1) * bf_lo(w.y) + bf_hi(a1) * bf_hi(w.y)
               + bf_lo(a2) * bf_lo(w.z) + bf_hi(a2) * bf_hi(w.z) + bf_lo(a3) * bf_lo(w.w) + bf_hi(a3) * bf_hi(w.w);
          if (t < 32) {
            asm volatile("ld.shared.v4.u32 {%0,%1,%2,%3}, [%4];" : "=r"(a0), "=r"(a1), "=r"(a2), "=r"(a3) : "r"(rbase + 96 * 128 + ((c ^ (t & 7)) << 4)));
            dot2 += bf_lo(a0) * bf_lo(w.x) + bf_hi(a0) * bf_hi(w.x) + bf_lo(a1) * bf_lo(w.y) + bf_hi(a1) * bf_hi(w.y)
                  + bf_lo(a2) * bf_lo(w.z) + bf_hi(a2) * bf_hi(w.z) + bf_lo(a3) * bf_lo(w.w) + bf_hi(a3) * bf_hi(w.w);
          }
        }
        __syncwarp();
        if (lane == 0) mbar_arrive(bars + (B_EMPTYA + slot) * 8);
        cnt++; if (++slot == 3) slot = 0;
      }
      named_bar(1, 96);
      asm volatile("st.shared.f32 [%0], %1;" ::"r"(sG + t * 4), "f"(1.f / (1.f + __expf(-dot))) : "memory");
      if (t < 32) asm volatile("st.shared.f32 [%0], %1;" ::"r"(sG + (96 + t) * 4), "f"(1.f / (1.f + __expf(-dot2))) : "memory");
      named_bar(1, 96);
      mbar_wait(bars + B_STGFULL * 8, tl & 1);
      const int ch = t & 7;
#pragma unroll 2
      for (int idx = t; idx < w1_nat * 1024; idx += 96) {
        const int a = idx >> 10, row = (idx >> 3) & 127;
        const int col = (w1_at0 + a) * 64 + ch * 8;
        uint4 bv = __ldg(reinterpret_cast<const uint4*>(b1 + col));
        uint32_t v[4];
        asm volatile("ld.shared.v4.u32 {%0,%1,%2,%3}, [%4];" : "=r"(v[0]), "=r"(v[1]), "=r"(v[2]), "=r"(v[3])
                     : "r"(stg + a * 16384 + row * 128 + ((ch ^ (row & 7)) << 4)));
        float gr; asm volatile("ld.shared.f32 %0, [%1];" : "=f"(gr) : "r"(sG + row * 4));
        float om = 1.f - gr;
        uint4 o;
        o.x = pack_bf16(om * mish_f(bf_lo(v[0]) + bf_lo(bv.x)), om * mish_f(bf_hi(v[0]) + bf_hi(bv.x)));
        o.y = pack_bf16(om * mish_f(bf_lo(v[1]) + bf_lo(bv.y)), om * mish_f(bf_hi(v[1]) + bf_hi(bv.y)));
        o.z = pack_bf16(om * mish_f(bf_lo(v[2]) + bf_lo(bv.z)), om * mish_f(bf_hi(v[2]) + bf_hi(bv.z)));
        o.w = pack_bf16(om * mish_f(bf_lo(v[3]) + bf_lo(bv.w)), om * mish_f(bf_hi(v[3]) + bf_hi(bv.w)));
        *reinterpret_cast<uint4*>(g_h + (size_t)(rbt * 128 + row) * FF + col) = o;
      }
      __threadfence();
      named_bar(1, 96);
      if (t == 0) flag_add(&g_flags[F_H + rbt]);
      if (lane == 0) mbar_arrive(bars + B_STGEMPTY * 8);
    }
    if (regular) {
      mbar_wait(bars + B_STGFULL * 8, 1);
      if (t == 0) {
        for (int a = 0; a < qkv_nat; a++) tma_store(&maps.qkv_st, stg + a * 16384, (qkv_at0 + a) * 64, rb * 128);
        asm volatile("cp.async.bulk.commit_group;" ::: "memory");
        asm volatile("cp.async.bulk.wait_group 0;" ::: "memory");
        fence_async();
        __threadfence();
        flag_add(&g_flags[F_QKV + rb]);
        flag_wait(&g_flags[F_QKV + rb], 8);
        if (rb > 0) flag_wait(&g_flags[F_QKV + rb - 1], 8);
        fence_async();
        uint32_t fb = bars + B_ATTFULL * 8;
        mbar_expect(fb, 128 * 160 + 2 * 142 * 160);
        tma_load(stg, &maps.qkv_ldq, fb, 80 * j, rb * 128);
        tma_load(stg + ATT_K_OFF, &maps.qkv_ldkv, fb, 640 + 80 * j, rb * 128 - 14);
        tma_load(stg + ATT_V_OFF, &maps.qkv_ldkv, fb, 1280 + 80 * j, rb * 128 - 14);
        finish_reader();
      }
      mbar_wait(bars + B_ATTFULL * 8, 0);
      const int hd = lane & 3, sub = lane >> 2;
      const float sc = 0.22360679774997896f * 1.4426950408889634f;
#pragma unroll 1
      for (int u = warp - 1; u < 8; u += 3) {
        const int s0 = u * 16 + (sub & 3) + 8 * (sub >> 2);
        float qa[20], qb[20], la[8], lb[8];
        load_row20(stg + s0 * 160 + hd * 40, qa);
        load_row20(stg + (s0 + 4) * 160 + hd * 40, qb);
#pragma unroll
        for (int m = 0; m < 10; m++) {
          float kf[20];
          load_row20(stg + ATT_K_OFF + (s0 + 18 - 2 * m) * 160 + hd * 40, kf);
          if (m < 8) { float d = 0.f;
#pragma unroll
            for (int i = 0; i < 20; i++) d += qb[i] * kf[i];
            lb[m] = d; }
          if (m >= 2) { float d = 0.f;
#pragma unroll
            for (int i = 0; i < 20; i++) d += qa[i] * kf[i];
            la[m - 2] = d; }
        }
        const int gs = rb * 128 + s0;
        float ma = -3.0e38f, mb = -3.0e38f;
#pragma unroll
        for (int m = 0; m < 8; m++) {
          la[m] = (gs - 2 * m >= 0) ? la[m] * sc : -3.0e38f;
          lb[m] = (gs + 4 - 2 * m >= 0) ? lb[m] * sc : -3.0e38f;
          ma = fmaxf(ma, la[m]); mb = fmaxf(mb, lb[m]);
        }
        float sa = 0.f, sb = 0.f;
#pragma unroll
        for (int m = 0; m < 8; m++) {
          la[m] = exp2f(la[m] - ma); lb[m] = exp2f(lb[m] - mb);
          sa += la[m]; sb += lb[m];
        }
        float ga, gb;
        asm volatile("ld.shared.f32 %0, [%1];" : "=f"(ga) : "r"(sG + s0 * 4));
        asm volatile("ld.shared.f32 %0, [%1];" : "=f"(gb) : "r"(sG + (s0 + 4) * 4));
        ga = ga / sa; gb = gb / sb;
        float oa[20], ob[20];
#pragma unroll
        for (int i = 0; i < 20; i++) { oa[i] = 0.f; ob[i] = 0.f; }
#pragma unroll
        for (int m = 0; m < 10; m++) {
          float vf[20];
          load_row20(stg + ATT_V_OFF + (s0 + 18 - 2 * m) * 160 + hd * 40, vf);
          if (m < 8) {
#pragma unroll
            for (int i = 0; i < 20; i++) ob[i] += lb[m] * vf[i]; }
          if (m >= 2) {
#pragma unroll
            for (int i = 0; i < 20; i++) oa[i] += la[m - 2] * vf[i]; }
        }
        uint2* pa = reinterpret_cast<uint2*>(g_o + (size_t)gs * DM + 80 * j + hd * 20);
        uint2* pb = reinterpret_cast<uint2*>(g_o + (size_t)(gs + 4) * DM + 80 * j + hd * 20);
#pragma unroll
        for (int i = 0; i < 5; i++) {
          pa[i] = make_uint2(pack_bf16(oa[4 * i] * ga, oa[4 * i + 1] * ga), pack_bf16(oa[4 * i + 2] * ga, oa[4 * i + 3] * ga));
          pb[i] = make_uint2(pack_bf16(ob[4 * i] * gb, ob[4 * i + 1] * gb), pack_bf16(ob[4 * i + 2] * gb, ob[4 * i + 3] * gb));
        }
      }
      __threadfence();
      named_bar(1, 96);
      if (t == 0) flag_add(&g_flags[F_O + rb]);
    }
   }
  } else {
    asm volatile("setmaxnreg.inc.sync.aligned.u32 200;");
    const int wg = wgi - 1;
    int slot = 0, cnt = 0;
    if (!regular) {
      for (int tl = 0; tl < 4; tl++)
        phase1_tile<64>(ring, bars, bars + B_FULLA * 8, bars + B_EMPTYA * 8, slot, cnt, tl, wg, warp, lane);
    } else {
      if (j < 6) phase1_tile<192>(ring, bars, bars + B_FULLA * 8, bars + B_EMPTYA * 8, slot, cnt, 0, wg, warp, lane);
      else       phase1_tile<256>(ring, bars, bars + B_FULLA * 8, bars + B_EMPTYA * 8, slot, cnt, 0, wg, warp, lane);
      cnt = 0;
      if (j < 6) phase1_tile<256>(ring, bars, bars + B_FULLB * 8, bars + B_EMPTYB * 8, slot, cnt, 1, wg, warp, lane);
      else       phase1_tile<192>(ring, bars, bars + B_FULLB * 8, bars + B_EMPTYB * 8, slot, cnt, 1, wg, warp, lane);
      float acc[80];
      slot = 3; cnt = 0;
      mainloop<160, 4, SLOT2>(acc, ring, bars + B_FULLC * 8, bars + B_EMPTYC * 8, slot, cnt, rank == 0 ? 19 : 18, wg, lane);
      const uint32_t peer = rank ^ 1;
      __syncwarp();
      if (lane == 0) mbar_arrive_cl(mapa(bars + B_PEERFREE * 8, peer));
      mbar_wait_cl(bars + B_PEERFREE * 8, 0);
      const int ct = tid - 128;
      const uint32_t rdst = mapa(ring + ct * 16, peer);
#pragma unroll
      for (int i = 0; i < 10; i++) {
        float v0 = rank == 0 ? acc[40 + 4 * i] : acc[4 * i], v1 = rank == 0 ? acc[41 + 4 * i] : acc[4 * i + 1];
        float v2 = rank == 0 ? acc[42 + 4 * i] : acc[4 * i + 2], v3 = rank == 0 ? acc[43 + 4 * i] : acc[4 * i + 3];
        asm volatile("st.shared::cluster.v4.f32 [%0], {%1,%2,%3,%4};" ::"r"(rdst + i * 4096), "f"(v0), "f"(v1), "f"(v2), "f"(v3) : "memory");
      }
      mbar_arrive_cl(mapa(bars + B_PEERDATA * 8, peer));
      mbar_wait_cl(bars + B_PEERDATA * 8, 0);
      const int row = rb2 * 128 + wg * 64 + warp * 16 + (lane >> 2);
#pragma unroll
      for (int i = 0; i < 10; i++) {
        float v0, v1, v2, v3;
        asm volatile("ld.shared.v4.f32 {%0,%1,%2,%3}, [%4];" : "=f"(v0), "=f"(v1), "=f"(v2), "=f"(v3) : "r"(ring + ct * 16 + i * 4096));
        v0 += rank == 0 ? acc[4 * i] : acc[40 + 4 * i]; v1 += rank == 0 ? acc[4 * i + 1] : acc[41 + 4 * i];
        v2 += rank == 0 ? acc[4 * i + 2] : acc[42 + 4 * i]; v3 += rank == 0 ? acc[4 * i + 3] : acc[43 + 4 * i];
        int c = (rank * 10 + i) * 8 + (lane & 3) * 2;
        int gc = (nt & 1) ? (c < 128 ? 160 * nt + 32 + c : 160 * nt + c - 128) : 160 * nt + c;
        *reinterpret_cast<uint32_t*>(out + (size_t)row * DM + gc) = pack_bf16(v0, v1);
        *reinterpret_cast<uint32_t*>(out + (size_t)(row + 8) * DM + gc) = pack_bf16(v2, v3);
      }
    }
  }
}

typedef CUresult (*EncFn)(CUtensorMap*, CUtensorMapDataType, cuuint32_t, void*, const cuuint64_t*, const cuuint64_t*,
                          const cuuint32_t*, const cuuint32_t*, CUtensorMapInterleave, CUtensorMapSwizzle,
                          CUtensorMapL2promotion, CUtensorMapFloatOOBfill);

void make_map(EncFn enc, CUtensorMap* m, const void* p, int cols, int rows, int bc, int br, bool swz) {
  cuuint64_t d[2] = {(cuuint64_t)cols, (cuuint64_t)rows};
  cuuint64_t s[1] = {(cuuint64_t)cols * 2};
  cuuint32_t b[2] = {(cuuint32_t)bc, (cuuint32_t)br};
  cuuint32_t e[2] = {1, 1};
  enc(m, CU_TENSOR_MAP_DATA_TYPE_BFLOAT16, 2, const_cast<void*>(p), d, s, b, e, CU_TENSOR_MAP_INTERLEAVE_NONE,
      swz ? CU_TENSOR_MAP_SWIZZLE_128B : CU_TENSOR_MAP_SWIZZLE_NONE, CU_TENSOR_MAP_L2_PROMOTION_L2_128B,
      CU_TENSOR_MAP_FLOAT_OOB_FILL_NONE);
}

}

extern "C" void kernel_launch(void* const* d_in, const int* in_sizes, int n_in, void* d_out, int out_size) {
  (void)in_sizes; (void)n_in; (void)out_size;
  static Maps maps;
  static bool ready = false;
  if (!ready) {
    EncFn enc = nullptr;
    cudaDriverEntryPointQueryResult q;
    cudaGetDriverEntryPoint("cuTensorMapEncodeTiled", (void**)&enc, cudaEnableDefault, &q);
    void *ph, *po, *pq;
    cudaGetSymbolAddress(&ph, g_h);
    cudaGetSymbolAddress(&po, g_o);
    cudaGetSymbolAddress(&pq, g_qkv);
    make_map(enc, &maps.x, d_in[0], DM, SEQ, 64, 128, true);
    make_map(enc, &maps.wqkv, d_in[1], QKVN, DM, 64, 64, true);
    make_map(enc, &maps.wo, d_in[2], DM, DM, 64, 64, true);
    make_map(enc, &maps.w1, d_in[4], FF, DM, 64, 64, true);
    make_map(enc, &maps.w2, d_in[6], DM, FF, 64, 64, true);
    make_map(enc, &maps.h, ph, FF, SEQ, 64, 128, true);
    make_map(enc, &maps.o, po, DM, SEQ, 64, 128, true);
    make_map(enc, &maps.qkv_st, pq, QKVN, SEQ, 64, 128, true);
    make_map(enc, &maps.qkv_ldq, pq, QKVN, SEQ, 80, 128, false);
    make_map(enc, &maps.qkv_ldkv, pq, QKVN, SEQ, 80, 142, false);
    cudaFuncSetAttribute(fused_kernel, cudaFuncAttributeMaxDynamicSharedMemorySize, SMEM_ALLOC);
    ready = true;
  }
  fused_kernel<<<NCTAS, NTHREADS, SMEM_ALLOC>>>(maps, (const __nv_bfloat16*)d_in[5], (const __nv_bfloat16*)d_in[7],
                                               (__nv_bfloat16*)d_out);
}
```

```cpp
#include <cuda_runtime.h>
#include <cuda.h>
#include <cuda_bf16.h>
#include <stdint.h>

namespace {

constexpr int SEQ = 2048, DM = 640, FF = 1728, QKVN = 1920;
constexpr int NTHREADS = 384;
constexpr int NREG_CTAS = 128;
constexpr int NCTAS = 132;

#define K_ATT 9

constexpr int RING_BYTES = 163840;
constexpr int SLOT1 = 49152;
constexpr int SLOT2 = 40960;
constexpr int SLOTX = 24576;
constexpr int STG_OFF = RING_BYTES;
constexpr int STG_BYTES = 66048;
constexpr int ATT_K_OFF = 20480;
constexpr int ATT_V_OFF = 43264;
constexpr int MISC_OFF = STG_OFF + STG_BYTES;
constexpr int SG_OFF = MISC_OFF + 256;
constexpr int SMEM_USED = SG_OFF + 1024;
constexpr int SMEM_ALLOC = SMEM_USED + 1024;

enum { B_FULL1 = 0, B_EMPTY1 = 6, B_FULL2 = 12, B_EMPTY2 = 16,
       B_STGFULL = 20, B_GREADY = 21, B_ATTFULL = 22, B_PEERFREE = 23, B_PEERDATA = 24, B_HDONE = 25, B_ODONE = 26,
       B_STGFREE = 27, B_COUNT = 28 };

enum { F_H = 0, F_QKV = 16, F_O = 32, F_FIN = 48 };
constexpr int FSTR = 32;

__device__ __nv_bfloat16 g_h[SEQ * FF];
__device__ __nv_bfloat16 g_o[SEQ * DM];
__device__ __nv_bfloat16 g_qkv[SEQ * QKVN];
__device__ unsigned g_flags[64 * 32];

struct Maps { CUtensorMap x, wqkv, w1, w2, wo, h, o, qkv_st, qkv_ldq, qkv_ldkv, o_st, out_st; };

__device__ __forceinline__ uint32_t s2u(const void* p) { return (uint32_t)__cvta_generic_to_shared(p); }
__device__ __forceinline__ void mbar_init(uint32_t b, int c) { asm volatile("mbarrier.init.shared::cta.b64 [%0], %1;" ::"r"(b), "r"(c)); }
__device__ __forceinline__ void mbar_expect(uint32_t b, int bytes) { asm volatile("mbarrier.arrive.expect_tx.shared::cta.b64 _, [%0], %1;" ::"r"(b), "r"(bytes) : "memory"); }
__device__ __forceinline__ void mbar_arrive(uint32_t b) { asm volatile("mbarrier.arrive.shared::cta.b64 _, [%0];" ::"r"(b) : "memory"); }
__device__ __forceinline__ bool mbar_try(uint32_t b, int par) {
  uint32_t ok;
  asm volatile("{\n.reg .pred p;\nmbarrier.try_wait.parity.shared::cta.b64 p, [%1], %2;\nselp.u32 %0, 1, 0, p;\n}" : "=r"(ok) : "r"(b), "r"(par) : "memory");
  return ok != 0;
}
__device__ __forceinline__ bool mbar_test(uint32_t b, int par) {
  uint32_t ok;
  asm volatile("{\n.reg .pred p;\nmbarrier.test_wait.parity.shared::cta.b64 p, [%1], %2;\nselp.u32 %0, 1, 0, p;\n}" : "=r"(ok) : "r"(b), "r"(par) : "memory");
  return ok != 0;
}
#define TRAP(c, e) __trap()
__device__ __forceinline__ void mbar_wait(uint32_t b, int par) {
  uint32_t n = 0;
  while (!mbar_try(b, par)) { if (++n > (1u << 22)) TRAP(1, (b & 255) / 8 + 1000 * par); }
}
__device__ __forceinline__ bool mbar_try_cl(uint32_t b, int par) {
  uint32_t ok;
  asm volatile("{\n.reg .pred p;\nmbarrier.try_wait.parity.acquire.cluster.shared::cta.b64 p, [%1], %2;\nselp.u32 %0, 1, 0, p;\n}" : "=r"(ok) : "r"(b), "r"(par) : "memory");
  return ok != 0;
}
__device__ __forceinline__ void mbar_wait_cl(uint32_t b, int par) {
  uint32_t n = 0;
  while (!mbar_try_cl(b, par)) { if (++n > (1u << 22)) TRAP(2, (b & 255) / 8); }
}
__device__ __forceinline__ uint32_t mapa(uint32_t a, uint32_t cta) { uint32_t r; asm volatile("mapa.shared::cluster.u32 %0, %1, %2;" : "=r"(r) : "r"(a), "r"(cta)); return r; }
__device__ __forceinline__ void mbar_arrive_cl(uint32_t remote) { asm volatile("mbarrier.arrive.release.cluster.shared::cluster.b64 _, [%0];" ::"r"(remote) : "memory"); }
__device__ __forceinline__ void tma_load(uint32_t dst, const CUtensorMap* m, uint32_t bar, int c0, int c1) {
  asm volatile("cp.async.bulk.tensor.2d.shared::cluster.global.mbarrier::complete_tx::bytes [%0], [%1, {%3,%4}], [%2];" ::"r"(dst), "l"(m), "r"(bar), "r"(c0), "r"(c1) : "memory");
}
__device__ __forceinline__ void tma_load3(uint32_t dst, const CUtensorMap* m, uint32_t bar, int c0, int c1) {
  asm volatile("cp.async.bulk.tensor.3d.shared::cluster.global.mbarrier::complete_tx::bytes [%0], [%1, {%3,%4,%5}], [%2];" ::"r"(dst), "l"(m), "r"(bar), "r"(c0), "r"(c1), "r"(0) : "memory");
}
__device__ __forceinline__ void tma_store3(const CUtensorMap* m, uint32_t src, int c0, int c1) {
  asm volatile("cp.async.bulk.tensor.3d.global.shared::cta.bulk_group [%0, {%2,%3,%4}], [%1];" ::"l"(m), "r"(src), "r"(c0), "r"(c1), "r"(0) : "memory");
}
__device__ __forceinline__ void tma_store(const CUtensorMap* m, uint32_t src, int c0, int c1) {
  asm volatile("cp.async.bulk.tensor.2d.global.shared::cta.bulk_group [%0, {%2,%3}], [%1];" ::"l"(m), "r"(src), "r"(c0), "r"(c1) : "memory");
}
__device__ __forceinline__ void fence_async() { asm volatile("fence.proxy.async.global;" ::: "memory"); }
__device__ __forceinline__ void fence_async_smem() { asm volatile("fence.proxy.async.shared::cta;" ::: "memory"); }
__device__ __forceinline__ void wg_fence() { asm volatile("wgmma.fence.sync.aligned;" ::: "memory"); }
__device__ __forceinline__ void wg_commit() { asm volatile("wgmma.commit_group.sync.aligned;" ::: "memory"); }
template <int N> __device__ __forceinline__ void wg_wait() { asm volatile("wgmma.wait_group.sync.aligned %0;" ::"n"(N) : "memory"); }
__device__ __forceinline__ void named_bar(int id, int n) { asm volatile("bar.sync %0, %1;" ::"r"(id), "r"(n) : "memory"); }
__device__ __forceinline__ unsigned ld_rlx(const unsigned* p) { unsigned v; asm volatile("ld.relaxed.gpu.global.u32 %0, [%1];" : "=r"(v) : "l"(p) : "memory"); return v; }
__device__ __forceinline__ void flag_add(unsigned* p) { asm volatile("red.relaxed.gpu.global.add.u32 [%0], 1;" ::"l"(p) : "memory"); }
__device__ __forceinline__ void flag_wait(const unsigned* p, unsigned target) {
  uint32_t n = 0;
  while (ld_rlx(p) < target) { __nanosleep(32); if (++n > (1u << 20)) TRAP(3, (unsigned)(p - g_flags)); }
}
__device__ __forceinline__ void bulk_commit_wait() {
  asm volatile("cp.async.bulk.commit_group;" ::: "memory");
  asm volatile("cp.async.bulk.wait_group 0;" ::: "memory");
}
__device__ __forceinline__ void finish_reader() {
  unsigned old = atomicAdd(&g_flags[F_FIN * FSTR], 1u);
  if (old == 2 * NREG_CTAS - 1) {
    for (int i = 0; i <= F_FIN; i++) g_flags[i * FSTR] = 0;
  }
}
#define TS(i)
#define TR()
__device__ __forceinline__ uint32_t pack_bf16(float a, float b) { __nv_bfloat162 t = __floats2bfloat162_rn(a, b); return *reinterpret_cast<uint32_t*>(&t); }
__device__ __forceinline__ float bf_lo(uint32_t v) { return __uint_as_float(v << 16); }
__device__ __forceinline__ float bf_hi(uint32_t v) { return __uint_as_float(v & 0xffff0000u); }

__device__ __forceinline__ uint64_t desc_a(uint32_t a) { return (uint64_t)((a & 0x3FFFF) >> 4) | (1ull << 16) | (64ull << 32) | (1ull << 62); }
__device__ __forceinline__ uint64_t desc_b(uint32_t a) { return (uint64_t)((a & 0x3FFFF) >> 4) | (512ull << 16) | (64ull << 32) | (1ull << 62); }

__device__ __forceinline__ void wgmma_n256(float (&d)[128], uint64_t da, uint64_t db, int sc) {
  asm volatile("{\n.reg .pred p;\nsetp.ne.b32 p, %130, 0;\n"
    "wgmma.mma_async.sync.aligned.m64n256k16.f32.bf16.bf16 {%0, %1, %2, %3, %4, %5, %6, %7, %8, %9, %10, %11, %12, %13, %14, %15, %16, %17, %18, %19, %20, %21, %22, %23, %24, %25, %26, %27, %28, %29, %30, %31, %32, %33, %34, %35, %36, %37, %38, %39, %40, %41, %42, %43, %44, %45, %46, %47, %48, %49, %50, %51, %52, %53, %54, %55, %56, %57, %58, %59, %60, %61, %62, %63, %64, %65, %66, %67, %68, %69, %70, %71, %72, %73, %74, %75, %76, %77, %78, %79, %80, %81, %82, %83, %84, %85, %86, %87, %88, %89, %90, %91, %92, %93, %94, %95, %96, %97, %98, %99, %100, %101, %102, %103, %104, %105, %106, %107, %108, %109, %110, %111, %112, %113, %114, %115, %116, %117, %118, %119, %120, %121, %122, %123, %124, %125, %126, %127}, %128, %129, p, 1, 1, 0, 1;\n}\n"
    : "+f"(d[0]), "+f"(d[1]), "+f"(d[2]), "+f"(d[3]), "+f"(d[4]), "+f"(d[5]), "+f"(d[6]), "+f"(d[7]), "+f"(d[8]), "+f"(d[9]), "+f"(d[10]), "+f"(d[11]), "+f"(d[12]), "+f"(d[13]), "+f"(d[14]), "+f"(d[15]), "+f"(d[16]), "+f"(d[17]), "+f"(d[18]), "+f"(d[19]), "+f"(d[20]), "+f"(d[21]), "+f"(d[22]), "+f"(d[23]), "+f"(d[24]), "+f"(d[25]), "+f"(d[26]), "+f"(d[27]), "+f"(d[28]), "+f"(d[29]), "+f"(d[30]), "+f"(d[31]), "+f"(d[32]), "+f"(d[33]), "+f"(d[34]), "+f"(d[35]), "+f"(d[36]), "+f"(d[37]), "+f"(d[38]), "+f"(d[39]), "+f"(d[40]), "+f"(d[41]), "+f"(d[42]), "+f"(d[43]), "+f"(d[44]), "+f"(d[45]), "+f"(d[46]), "+f"(d[47]), "+f"(d[48]), "+f"(d[49]), "+f"(d[50]), "+f"(d[51]), "+f"(d[52]), "+f"(d[53]), "+f"(d[54]), "+f"(d[55]), "+f"(d[56]), "+f"(d[57]), "+f"(d[58]), "+f"(d[59]), "+f"(d[60]), "+f"(d[61]), "+f"(d[62]), "+f"(d[63]), "+f"(d[64]), "+f"(d[65]), "+f"(d[66]), "+f"(d[67]), "+f"(d[68]), "+f"(d[69]), "+f"(d[70]), "+f"(d[71]), "+f"(d[72]), "+f"(d[73]), "+f"(d[74]), "+f"(d[75]), "+f"(d[76]), "+f"(d[77]), "+f"(d[78]), "+f"(d[79]), "+f"(d[80]), "+f"(d[81]), "+f"(d[82]), "+f"(d[83]), "+f"(d[84]), "+f"(d[85]), "+f"(d[86]), "+f"(d[87]), "+f"(d[88]), "+f"(d[89]), "+f"(d[90]), "+f"(d[91]), "+f"(d[92]), "+f"(d[93]), "+f"(d[94]), "+f"(d[95]), "+f"(d[96]), "+f"(d[97]), "+f"(d[98]), "+f"(d[99]), "+f"(d[100]), "+f"(d[101]), "+f"(d[102]), "+f"(d[103]), "+f"(d[104]), "+f"(d[105]), "+f"(d[106]), "+f"(d[107]), "+f"(d[108]), "+f"(d[109]), "+f"(d[110]), "+f"(d[111]), "+f"(d[112]), "+f"(d[113]), "+f"(d[114]), "+f"(d[115]), "+f"(d[116]), "+f"(d[117]), "+f"(d[118]), "+f"(d[119]), "+f"(d[120]), "+f"(d[121]), "+f"(d[122]), "+f"(d[123]), "+f"(d[124]), "+f"(d[125]), "+f"(d[126]), "+f"(d[127])
    : "l"(da), "l"(db), "r"(sc));
}
__device__ __forceinline__ void wgmma_n192(float (&d)[96], uint64_t da, uint64_t db, int sc) {
  asm volatile("{\n.reg .pred p;\nsetp.ne.b32 p, %98, 0;\n"
    "wgmma.mma_async.sync.aligned.m64n192k16.f32.bf16.bf16 {%0, %1, %2, %3, %4, %5, %6, %7, %8, %9, %10, %11, %12, %13, %14, %15, %16, %17, %18, %19, %20, %21, %22, %23, %24, %25, %26, %27, %28, %29, %30, %31, %32, %33, %34, %35, %36, %37, %38, %39, %40, %41, %42, %43, %44, %45, %46, %47, %48, %49, %50, %51, %52, %53, %54, %55, %56, %57, %58, %59, %60, %61, %62, %63, %64, %65, %66, %67, %68, %69, %70, %71, %72, %73, %74, %75, %76, %77, %78, %79, %80, %81, %82, %83, %84, %85, %86, %87, %88, %89, %90, %91, %92, %93, %94, %95}, %96, %97, p, 1, 1, 0, 1;\n}\n"
    : "+f"(d[0]), "+f"(d[1]), "+f"(d[2]), "+f"(d[3]), "+f"(d[4]), "+f"(d[5]), "+f"(d[6]), "+f"(d[7]), "+f"(d[8]), "+f"(d[9]), "+f"(d[10]), "+f"(d[11]), "+f"(d[12]), "+f"(d[13]), "+f"(d[14]), "+f"(d[15]), "+f"(d[16]), "+f"(d[17]), "+f"(d[18]), "+f"(d[19]), "+f"(d[20]), "+f"(d[21]), "+f"(d[22]), "+f"(d[23]), "+f"(d[24]), "+f"(d[25]), "+f"(d[26]), "+f"(d[27]), "+f"(d[28]), "+f"(d[29]), "+f"(d[30]), "+f"(d[31]), "+f"(d[32]), "+f"(d[33]), "+f"(d[34]), "+f"(d[35]), "+f"(d[36]), "+f"(d[37]), "+f"(d[38]), "+f"(d[39]), "+f"(d[40]), "+f"(d[41]), "+f"(d[42]), "+f"(d[43]), "+f"(d[44]), "+f"(d[45]), "+f"(d[46]), "+f"(d[47]), "+f"(d[48]), "+f"(d[49]), "+f"(d[50]), "+f"(d[51]), "+f"(d[52]), "+f"(d[53]), "+f"(d[54]), "+f"(d[55]), "+f"(d[56]), "+f"(d[57]), "+f"(d[58]), "+f"(d[59]), "+f"(d[60]), "+f"(d[61]), "+f"(d[62]), "+f"(d[63]), "+f"(d[64]), "+f"(d[65]), "+f"(d[66]), "+f"(d[67]), "+f"(d[68]), "+f"(d[69]), "+f"(d[70]), "+f"(d[71]), "+f"(d[72]), "+f"(d[73]), "+f"(d[74]), "+f"(d[75]), "+f"(d[76]), "+f"(d[77]), "+f"(d[78]), "+f"(d[79]), "+f"(d[80]), "+f"(d[81]), "+f"(d[82]), "+f"(d[83]), "+f"(d[84]), "+f"(d[85]), "+f"(d[86]), "+f"(d[87]), "+f"(d[88]), "+f"(d[89]), "+f"(d[90]), "+f"(d[91]), "+f"(d[92]), "+f"(d[93]), "+f"(d[94]), "+f"(d[95])
    : "l"(da), "l"(db), "r"(sc));
}
__device__ __forceinline__ void wgmma_n160(float (&d)[80], uint64_t da, uint64_t db, int sc) {
  asm volatile("{\n.reg .pred p;\nsetp.ne.b32 p, %82, 0;\n"
    "wgmma.mma_async.sync.aligned.m64n160k16.f32.bf16.bf16 {%0, %1, %2, %3, %4, %5, %6, %7, %8, %9, %10, %11, %12, %13, %14, %15, %16, %17, %18, %19, %20, %21, %22, %23, %24, %25, %26, %27, %28, %29, %30, %31, %32, %33, %34, %35, %36, %37, %38, %39, %40, %41, %42, %43, %44, %45, %46, %47, %48, %49, %50, %51, %52, %53, %54, %55, %56, %57, %58, %59, %60, %61, %62, %63, %64, %65, %66, %67, %68, %69, %70, %71, %72, %73, %74, %75, %76, %77, %78, %79}, %80, %81, p, 1, 1, 0, 1;\n}\n"
    : "+f"(d[0]), "+f"(d[1]), "+f"(d[2]), "+f"(d[3]), "+f"(d[4]), "+f"(d[5]), "+f"(d[6]), "+f"(d[7]), "+f"(d[8]), "+f"(d[9]), "+f"(d[10]), "+f"(d[11]), "+f"(d[12]), "+f"(d[13]), "+f"(d[14]), "+f"(d[15]), "+f"(d[16]), "+f"(d[17]), "+f"(d[18]), "+f"(d[19]), "+f"(d[20]), "+f"(d[21]), "+f"(d[22]), "+f"(d[23]), "+f"(d[24]), "+f"(d[25]), "+f"(d[26]), "+f"(d[27]), "+f"(d[28]), "+f"(d[29]), "+f"(d[30]), "+f"(d[31]), "+f"(d[32]), "+f"(d[33]), "+f"(d[34]), "+f"(d[35]), "+f"(d[36]), "+f"(d[37]), "+f"(d[38]), "+f"(d[39]), "+f"(d[40]), "+f"(d[41]), "+f"(d[42]), "+f"(d[43]), "+f"(d[44]), "+f"(d[45]), "+f"(d[46]), "+f"(d[47]), "+f"(d[48]), "+f"(d[49]), "+f"(d[50]), "+f"(d[51]), "+f"(d[52]), "+f"(d[53]), "+f"(d[54]), "+f"(d[55]), "+f"(d[56]), "+f"(d[57]), "+f"(d[58]), "+f"(d[59]), "+f"(d[60]), "+f"(d[61]), "+f"(d[62]), "+f"(d[63]), "+f"(d[64]), "+f"(d[65]), "+f"(d[66]), "+f"(d[67]), "+f"(d[68]), "+f"(d[69]), "+f"(d[70]), "+f"(d[71]), "+f"(d[72]), "+f"(d[73]), "+f"(d[74]), "+f"(d[75]), "+f"(d[76]), "+f"(d[77]), "+f"(d[78]), "+f"(d[79])
    : "l"(da), "l"(db), "r"(sc));
}
__device__ __forceinline__ void wgmma_n128(float (&d)[64], uint64_t da, uint64_t db, int sc) {
  asm volatile("{\n.reg .pred p;\nsetp.ne.b32 p, %66, 0;\n"
    "wgmma.mma_async.sync.aligned.m64n128k16.f32.bf16.bf16 {%0, %1, %2, %3, %4, %5, %6, %7, %8, %9, %10, %11, %12, %13, %14, %15, %16, %17, %18, %19, %20, %21, %22, %23, %24, %25, %26, %27, %28, %29, %30, %31, %32, %33, %34, %35, %36, %37, %38, %39, %40, %41, %42, %43, %44, %45, %46, %47, %48, %49, %50, %51, %52, %53, %54, %55, %56, %57, %58, %59, %60, %61, %62, %63}, %64, %65, p, 1, 1, 0, 1;\n}\n"
    : "+f"(d[0]), "+f"(d[1]), "+f"(d[2]), "+f"(d[3]), "+f"(d[4]), "+f"(d[5]), "+f"(d[6]), "+f"(d[7]), "+f"(d[8]), "+f"(d[9]), "+f"(d[10]), "+f"(d[11]), "+f"(d[12]), "+f"(d[13]), "+f"(d[14]), "+f"(d[15]), "+f"(d[16]), "+f"(d[17]), "+f"(d[18]), "+f"(d[19]), "+f"(d[20]), "+f"(d[21]), "+f"(d[22]), "+f"(d[23]), "+f"(d[24]), "+f"(d[25]), "+f"(d[26]), "+f"(d[27]), "+f"(d[28]), "+f"(d[29]), "+f"(d[30]), "+f"(d[31]), "+f"(d[32]), "+f"(d[33]), "+f"(d[34]), "+f"(d[35]), "+f"(d[36]), "+f"(d[37]), "+f"(d[38]), "+f"(d[39]), "+f"(d[40]), "+f"(d[41]), "+f"(d[42]), "+f"(d[43]), "+f"(d[44]), "+f"(d[45]), "+f"(d[46]), "+f"(d[47]), "+f"(d[48]), "+f"(d[49]), "+f"(d[50]), "+f"(d[51]), "+f"(d[52]), "+f"(d[53]), "+f"(d[54]), "+f"(d[55]), "+f"(d[56]), "+f"(d[57]), "+f"(d[58]), "+f"(d[59]), "+f"(d[60]), "+f"(d[61]), "+f"(d[62]), "+f"(d[63])
    : "l"(da), "l"(db), "r"(sc));
}
__device__ __forceinline__ void wgmma_n64(float (&d)[32], uint64_t da, uint64_t db, int sc) {
  asm volatile("{\n.reg .pred p;\nsetp.ne.b32 p, %34, 0;\n"
    "wgmma.mma_async.sync.aligned.m64n64k16.f32.bf16.bf16 {%0, %1, %2, %3, %4, %5, %6, %7, %8, %9, %10, %11, %12, %13, %14, %15, %16, %17, %18, %19, %20, %21, %22, %23, %24, %25, %26, %27, %28, %29, %30, %31}, %32, %33, p, 1, 1, 0, 1;\n}\n"
    : "+f"(d[0]), "+f"(d[1]), "+f"(d[2]), "+f"(d[3]), "+f"(d[4]), "+f"(d[5]), "+f"(d[6]), "+f"(d[7]), "+f"(d[8]), "+f"(d[9]), "+f"(d[10]), "+f"(d[11]), "+f"(d[12]), "+f"(d[13]), "+f"(d[14]), "+f"(d[15]), "+f"(d[16]), "+f"(d[17]), "+f"(d[18]), "+f"(d[19]), "+f"(d[20]), "+f"(d[21]), "+f"(d[22]), "+f"(d[23]), "+f"(d[24]), "+f"(d[25]), "+f"(d[26]), "+f"(d[27]), "+f"(d[28]), "+f"(d[29]), "+f"(d[30]), "+f"(d[31])
    : "l"(da), "l"(db), "r"(sc));
}
__device__ __forceinline__ void wgmma_n32(float (&d)[16], uint64_t da, uint64_t db, int sc) {
  asm volatile("{\n.reg .pred p;\nsetp.ne.b32 p, %18, 0;\n"
    "wgmma.mma_async.sync.aligned.m64n32k16.f32.bf16.bf16 {%0, %1, %2, %3, %4, %5, %6, %7, %8, %9, %10, %11, %12, %13, %14, %15}, %16, %17, p, 1, 1, 0, 1;\n}\n"
    : "+f"(d[0]), "+f"(d[1]), "+f"(d[2]), "+f"(d[3]), "+f"(d[4]), "+f"(d[5]), "+f"(d[6]), "+f"(d[7]), "+f"(d[8]), "+f"(d[9]), "+f"(d[10]), "+f"(d[11]), "+f"(d[12]), "+f"(d[13]), "+f"(d[14]), "+f"(d[15])
    : "l"(da), "l"(db), "r"(sc));
}

template <int N> struct MMA;
template <> struct MMA<256> { static __device__ __forceinline__ void run(float (&d)[128], uint64_t a, uint64_t b, int s) { wgmma_n256(d, a, b, s); } };
template <> struct MMA<192> { static __device__ __forceinline__ void run(float (&d)[96], uint64_t a, uint64_t b, int s) { wgmma_n192(d, a, b, s); } };
template <> struct MMA<160> { static __device__ __forceinline__ void run(float (&d)[80], uint64_t a, uint64_t b, int s) { wgmma_n160(d, a, b, s); } };
template <> struct MMA<64>  { static __device__ __forceinline__ void run(float (&d)[32], uint64_t a, uint64_t b, int s) { wgmma_n64(d, a, b, s); } };

template <int NS, int SLOTB, class ISSUE, class BG>
__device__ __forceinline__ void mainloop(uint32_t ring, uint32_t fullb, uint32_t emptyb, int& slot, int& cnt, int nk,
                                         int wg, int lane, ISSUE&& issue, BG&& bg) {
  int prev = -1;
  for (int k = 0; k < nk; k++) {
    if (!mbar_test(fullb + slot * 8, (cnt / NS) & 1)) {
      if (prev >= 0) {
        wg_wait<0>();
        if (lane == 0) mbar_arrive(emptyb + prev * 8);
        prev = -1;
      }
      mbar_wait(fullb + slot * 8, (cnt / NS) & 1);
    }
    uint32_t base = ring + slot * SLOTB;
    TR();
    wg_fence();
    issue(desc_a(base + wg * 8192), desc_b(base + 16384));
    wg_commit();
    wg_wait<1>();
    if (prev >= 0 && lane == 0) mbar_arrive(emptyb + prev * 8);
    bg(k);
    prev = slot;
    cnt++;
    if (++slot == NS) slot = 0;
  }
  wg_wait<0>();
  if (lane == 0) mbar_arrive(emptyb + prev * 8);
}
template <int R> __device__ __forceinline__ void zero_acc(float (&a)[R]) {
#pragma unroll
  for (int i = 0; i < R; i++) a[i] = 0.f;
}
template <int R> __device__ __forceinline__ void pin_acc(float (&a)[R]) {
#pragma unroll
  for (int i = 0; i < R; i++) asm volatile("" : "+f"(a[i])::"memory");
}
template <int N, int NS, int SLOTB, class BG>
__device__ __forceinline__ void tile_loop(float (&acc)[N / 2], uint32_t ring, uint32_t fullb, uint32_t emptyb,
                                          int& slot, int& cnt, int wg, int lane, BG&& bg) {
  zero_acc(acc);
  mainloop<NS, SLOTB>(ring, fullb, emptyb, slot, cnt, 10, wg, lane, [&](uint64_t da, uint64_t db) {
#pragma unroll
    for (int kk = 0; kk < 4; kk++) MMA<N>::run(acc, da + kk * 2, db + kk * 128, 1);
  }, bg);
  pin_acc(acc);
}

template <int N>
__device__ __forceinline__ void dump_tile(float (&acc)[N / 2], uint32_t stg, int wg, int warp, int lane) {
  int row = wg * 64 + warp * 16 + (lane & 7) + ((lane >> 3) & 1) * 8;
  uint32_t rbase = stg + row * 128;
  int csel = lane >> 4;
#pragma unroll
  for (int jb = 0; jb < N / 8; jb += 2) {
    uint32_t r0 = pack_bf16(acc[4 * jb + 0], acc[4 * jb + 1]);
    uint32_t r1 = pack_bf16(acc[4 * jb + 2], acc[4 * jb + 3]);
    uint32_t r2 = pack_bf16(acc[4 * jb + 4], acc[4 * jb + 5]);
    uint32_t r3 = pack_bf16(acc[4 * jb + 6], acc[4 * jb + 7]);
    int cb = jb + csel;
    uint32_t addr = rbase + (cb >> 3) * 16384 + (((cb & 7) ^ (row & 7)) << 4);
    asm volatile("stmatrix.sync.aligned.m8n8.x4.shared.b16 [%0], {%1,%2,%3,%4};" ::"r"(addr), "r"(r0), "r"(r1), "r"(r2), "r"(r3) : "memory");
  }
}

__device__ __forceinline__ float ex2f(float x) { float y; asm("ex2.approx.ftz.f32 %0, %1;" : "=f"(y) : "f"(x)); return y; }
__device__ __forceinline__ float rcpf(float x) { float y; asm("rcp.approx.ftz.f32 %0, %1;" : "=f"(y) : "f"(x)); return y; }

__device__ __forceinline__ float mish_f(float x, float om, float om2) {
  float e = ex2f(x * 1.4426950408889634f);
  float r = rcpf(fmaf(e, e + 2.f, 2.f));
  return fmaf(x * om2, r, x * om);
}

__device__ __forceinline__ void mma16816(float (&c)[4], uint32_t a0, uint32_t a1, uint32_t a2, uint32_t a3, uint32_t b0, uint32_t b1) {
  asm volatile("mma.sync.aligned.m16n8k16.row.col.f32.bf16.bf16.f32 {%0,%1,%2,%3}, {%4,%5,%6,%7}, {%8,%9}, {%0,%1,%2,%3};"
               : "+f"(c[0]), "+f"(c[1]), "+f"(c[2]), "+f"(c[3]) : "r"(a0), "r"(a1), "r"(a2), "r"(a3), "r"(b0), "r"(b1));
}

__device__ __forceinline__ void ldsm4(uint32_t (&r)[4], uint32_t a) {
  asm volatile("ldmatrix.sync.aligned.m8n8.x4.shared.b16 {%0,%1,%2,%3}, [%4];" : "=r"(r[0]), "=r"(r[1]), "=r"(r[2]), "=r"(r[3]) : "r"(a) : "memory");
}
__device__ __forceinline__ void ldsm4t(uint32_t (&r)[4], uint32_t a) {
  asm volatile("ldmatrix.sync.aligned.m8n8.x4.trans.shared.b16 {%0,%1,%2,%3}, [%4];" : "=r"(r[0]), "=r"(r[1]), "=r"(r[2]), "=r"(r[3]) : "r"(a) : "memory");
}
__device__ __forceinline__ void ldsm2(uint32_t (&r)[2], uint32_t a) {
  asm volatile("ldmatrix.sync.aligned.m8n8.x2.shared.b16 {%0,%1}, [%2];" : "=r"(r[0]), "=r"(r[1]) : "r"(a) : "memory");
}

__device__ __forceinline__ uint4* mish_ptr(uint8_t* stp, int s, int i, int ct) {
  const int row = (ct >> 3) + 64 * (s & 1) + 32 * i;
  return reinterpret_cast<uint4*>(stp + (s >> 1) * 16384 + row * 128 + (((ct & 7) ^ (row & 7)) << 4));
}
__device__ __forceinline__ void mish_slice(uint8_t* stp, const float (&omr)[4], const uint4 bv, const uint4 (&v)[2], int s, int ct) {
  const float bb[8] = {bf_lo(bv.x), bf_hi(bv.x), bf_lo(bv.y), bf_hi(bv.y), bf_lo(bv.z), bf_hi(bv.z), bf_lo(bv.w), bf_hi(bv.w)};
#pragma unroll
  for (int i = 0; i < 2; i++) {
    const float om = (s & 1) ? omr[2 + i] : omr[i], om2 = -2.f * om;
    uint4 o;
    o.x = pack_bf16(mish_f(bf_lo(v[i].x) + bb[0], om, om2), mish_f(bf_hi(v[i].x) + bb[1], om, om2));
    o.y = pack_bf16(mish_f(bf_lo(v[i].y) + bb[2], om, om2), mish_f(bf_hi(v[i].y) + bb[3], om, om2));
    o.z = pack_bf16(mish_f(bf_lo(v[i].z) + bb[4], om, om2), mish_f(bf_hi(v[i].z) + bb[5], om, om2));
    o.w = pack_bf16(mish_f(bf_lo(v[i].w) + bb[6], om, om2), mish_f(bf_hi(v[i].w) + bb[7], om, om2));
    *mish_ptr(stp, s, i, ct) = o;
  }
}

__device__ __forceinline__ void warp_done(uint32_t bar, int lane) {
  fence_async_smem();
  __syncwarp();
  if (lane == 0) mbar_arrive(bar);
}

__global__ void __cluster_dims__(2, 1, 1) __launch_bounds__(NTHREADS, 1)
fused_kernel(const __grid_constant__ Maps maps, const __nv_bfloat16* __restrict__ b1,
             const __nv_bfloat16* __restrict__ gate_w, const uint8_t* __restrict__ wqkv_raw,
             const uint8_t* __restrict__ w2_raw, const uint8_t* __restrict__ wo_raw) {
  extern __shared__ uint8_t smem_raw[];
  const uint32_t ring = (s2u(smem_raw) + 1023) & ~1023u;
  const uint32_t bars = ring + MISC_OFF;
  uint8_t* const sp = smem_raw + (ring - s2u(smem_raw));
  const int tid = threadIdx.x, wgi = tid >> 7, warp = (tid >> 5) & 3, lane = tid & 31;
  const int cta = blockIdx.x;
  const bool regular = cta < NREG_CTAS;
  const int rb = cta & 15, j = cta >> 4;
  const int nw1 = j < 6 ? 4 : (j == 6 ? 3 : 0);
  const int w1_at0 = 4 * j;
  const int q1_at0 = j == 6 ? 0 : 1;
  const int q2_at0 = 5 + 3 * j;
  const int xrb = (cta - NREG_CTAS) * 4;
  const int rank = cta & 1, pr = cta >> 1;
  const int rb2 = pr & 15, nt = pr >> 4;

  if (tid == 0) {
    for (int i = 0; i < 6; i++) { mbar_init(bars + (B_FULL1 + i) * 8, 1); mbar_init(bars + (B_EMPTY1 + i) * 8, regular ? 11 : 8); }
    for (int i = 0; i < 4; i++) { mbar_init(bars + (B_FULL2 + i) * 8, 1); mbar_init(bars + (B_EMPTY2 + i) * 8, 8); }
    mbar_init(bars + B_STGFULL * 8, 1);
    mbar_init(bars + B_STGFREE * 8, regular ? 2 : 1);
    mbar_init(bars + B_GREADY * 8, 3);
    mbar_init(bars + B_ATTFULL * 8, 1);
    mbar_init(bars + B_PEERFREE * 8, 1);
    mbar_init(bars + B_PEERDATA * 8, 1);
    mbar_init(bars + B_HDONE * 8, 8);
    mbar_init(bars + B_ODONE * 8, 8);
    mbar_expect(bars + B_PEERDATA * 8, 40960);
    asm volatile("fence.mbarrier_init.release.cluster;" ::: "memory");
  }
  if (tid == 32) {
    const CUtensorMap* mp = &maps.x;
    for (int i = 0; i < 12; i++) asm volatile("prefetch.tensormap [%0];" ::"l"(mp + i) : "memory");
  }
  if (tid == 64 && regular) {
    asm volatile("cp.async.bulk.prefetch.L2.global [%0], %1;" ::"l"(wqkv_raw + cta * 19200), "r"(19200) : "memory");
    asm volatile("cp.async.bulk.prefetch.L2.global [%0], %1;" ::"l"(w2_raw + cta * 17280), "r"(17280) : "memory");
    asm volatile("cp.async.bulk.prefetch.L2.global [%0], %1;" ::"l"(wo_raw + cta * 6400), "r"(6400) : "memory");
  }
  __syncthreads();
  asm volatile("barrier.cluster.arrive.release.aligned;" ::: "memory");

  if (wgi == 0) {
   asm volatile("setmaxnreg.dec.sync.aligned.u32 104;");
   const uint32_t stg = ring + STG_OFF;
   if (tid < 32) {
    if (tid == 0) {
      if (!regular) {
        int slot = 0;
        for (int i = 0; i < 40; i++) {
          mbar_wait(bars + (B_EMPTY1 + slot) * 8, ((i / 6) & 1) ^ 1);
          uint32_t base = ring + slot * SLOTX, fb = bars + (B_FULL1 + slot) * 8;
          const int t = i / 10, k = i - t * 10;
          mbar_expect(fb, SLOTX);
          tma_load(base, &maps.x, fb, k * 64, (xrb + t) * 128);
          tma_load(base + 16384, &maps.wqkv, fb, 29 * 64, k * 64);
          if (++slot == 6) slot = 0;
        }
      } else {
        for (int k = 0; k < 10; k++) {
          const int slot = k & 3;
          mbar_wait(bars + (B_EMPTY1 + slot) * 8, ((k >> 2) & 1) ^ 1);
          uint32_t base = ring + slot * SLOT1, fb = bars + (B_FULL1 + slot) * 8;
          mbar_expect(fb, SLOT1);
          tma_load(base, &maps.x, fb, k * 64, rb * 128);
          for (int a = 0; a < 4; a++) {
            if (a < nw1) tma_load(base + 16384 + a * 8192, &maps.w1, fb, (w1_at0 + a) * 64, k * 64);
            else tma_load(base + 16384 + a * 8192, &maps.wqkv, fb, (q1_at0 + a - nw1) * 64, k * 64);
          }
        }
        const int nh = rank == 0 ? 14 : 13, h0 = rank == 0 ? 0 : 14, o0 = rank == 0 ? 0 : 5;
        const int c0 = (nt & 1) ? 160 * nt + 32 : 160 * nt;
        const int c2 = (nt & 1) ? 160 * nt - 32 : 160 * nt + 128;
        for (int i = 0; i < 10 + nh + 5; i++) {
          const int slot = (i + 3) & 3;
          if (i < 4) {
            if (i == 0) { mbar_wait(bars + (B_EMPTY1 + 2) * 8, 1); mbar_wait(bars + (B_EMPTY1 + 3) * 8, 1); }
            else if (i == 1) mbar_wait(bars + (B_EMPTY1 + 0) * 8, 0);
            else if (i == 2) mbar_wait(bars + (B_EMPTY1 + 1) * 8, 0);
          } else mbar_wait(bars + (B_EMPTY2 + slot) * 8, ((i >> 2) & 1) ^ 1);
          uint32_t base = ring + slot * SLOT2, fb = bars + (B_FULL2 + slot) * 8;
          if (i < 10) {
            mbar_expect(fb, SLOT2);
            tma_load(base, &maps.x, fb, i * 64, rb * 128);
            for (int a = 0; a < 3; a++) tma_load(base + 16384 + a * 8192, &maps.wqkv, fb, (q2_at0 + a) * 64, i * 64);
          } else {
            const int p = i - 10;
            if (p == 0) { TS(16); flag_wait(&g_flags[(F_H + rb2) * FSTR], 7); TS(17); fence_async(); }
            if (p == nh) { TS(18); flag_wait(&g_flags[(F_O + rb2) * FSTR], 8); TS(19); fence_async(); }
            mbar_expect(fb, SLOT2);
            const bool hp = p < nh;
            const int kc = (hp ? h0 + p : o0 + p - nh) * 64;
            const CUtensorMap* ma = hp ? &maps.h : &maps.o;
            const CUtensorMap* mb = hp ? &maps.w2 : &maps.wo;
            tma_load(base, ma, fb, kc, rb2 * 128);
            tma_load(base + 16384, mb, fb, c0, kc);
            tma_load(base + 16384 + 8192, mb, fb, c0 + 64, kc);
            tma_load(base + 16384 + 16384, mb, fb, c2, kc);
          }
        }
        finish_reader();
      }
    }
    __syncwarp();
    asm volatile("barrier.cluster.wait.acquire.aligned;" ::: "memory");
   } else if (!regular) {
    asm volatile("barrier.cluster.wait.acquire.aligned;" ::: "memory");
    if (tid == 32) {
      for (int t = 0; t < 4; t++) {
        mbar_wait(bars + B_STGFULL * 8, t & 1);
        tma_store(&maps.qkv_st, stg, 29 * 64, (xrb + t) * 128);
        bulk_commit_wait();
        mbar_arrive(bars + B_STGFREE * 8);
        flag_add(&g_flags[(F_QKV + xrb + t) * FSTR]);
      }
    }
   } else {
    const int t = tid - 32;
    float* const sGp = reinterpret_cast<float*>(sp + SG_OFF);
    {
      const int ch = t & 7, r0 = t >> 3;
      float dot[11];
#pragma unroll
      for (int i = 0; i < 11; i++) dot[i] = 0.f;
      for (int k = 0; k < 10; k++) {
        uint4 w = __ldg(reinterpret_cast<const uint4*>(gate_w + k * 64 + ch * 8));
        mbar_wait(bars + (B_FULL1 + (k & 3)) * 8, (k >> 2) & 1);
        const uint8_t* abase = sp + (k & 3) * SLOT1;
        uint4 a[11];
#pragma unroll
        for (int i = 0; i < 11; i++) {
          int row = min(r0 + 12 * i, 127);
          a[i] = *reinterpret_cast<const uint4*>(abase + row * 128 + ((ch ^ (row & 7)) << 4));
        }
        __syncwarp();
        if (lane == 0) mbar_arrive(bars + (B_EMPTY1 + (k & 3)) * 8);
#pragma unroll
        for (int i = 0; i < 11; i++)
          dot[i] += bf_lo(a[i].x) * bf_lo(w.x) + bf_hi(a[i].x) * bf_hi(w.x) + bf_lo(a[i].y) * bf_lo(w.y) + bf_hi(a[i].y) * bf_hi(w.y)
                  + bf_lo(a[i].z) * bf_lo(w.z) + bf_hi(a[i].z) * bf_hi(w.z) + bf_lo(a[i].w) * bf_lo(w.w) + bf_hi(a[i].w) * bf_hi(w.w);
      }
#pragma unroll
      for (int i = 0; i < 11; i++) {
        float d = dot[i];
        d += __shfl_xor_sync(0xffffffffu, d, 1); d += __shfl_xor_sync(0xffffffffu, d, 2); d += __shfl_xor_sync(0xffffffffu, d, 4);
        int row = r0 + 12 * i;
        if (ch == 0 && row < 128) sGp[row] = rcpf(1.f + ex2f(-1.4426950408889634f * d));
      }
      __syncwarp();
      if (lane == 0) mbar_arrive(bars + B_GREADY * 8);
      if (t == 0) TS(8);
    }
    asm volatile("barrier.cluster.wait.acquire.aligned;" ::: "memory");
    if (t == 32) {
      for (int a = 0; a < nw1; a++) {
        mbar_wait(bars + B_HDONE * 8, a & 1);
        tma_store(&maps.h, stg + a * 16384, (w1_at0 + a) * 64, rb * 128);
      }
      if (nw1 > 0) { bulk_commit_wait(); flag_add(&g_flags[(F_H + rb) * FSTR]); }
      mbar_arrive(bars + B_STGFREE * 8);
      TS(10);
      mbar_wait(bars + B_ODONE * 8, 0);
      TS(28);
      tma_store3(&maps.o_st, stg, 80 * j, rb * 64);
      bulk_commit_wait();
      flag_add(&g_flags[(F_O + rb) * FSTR]);
      mbar_arrive_cl(mapa(bars + B_PEERFREE * 8, rank ^ 1));
      TS(15);
    } else if (t == 0) {
      mbar_wait(bars + B_STGFULL * 8, 0);
      if (nw1 < 4) {
        for (int a = nw1; a < 4; a++) tma_store(&maps.qkv_st, stg + a * 16384, (q1_at0 + a - nw1) * 64, rb * 128);
        bulk_commit_wait();
        flag_add(&g_flags[(F_QKV + rb) * FSTR]);
      }
      mbar_arrive(bars + B_STGFREE * 8);
      mbar_wait(bars + B_STGFULL * 8, 1);
      TS(11);
      for (int a = 0; a < 3; a++) tma_store(&maps.qkv_st, stg + a * 16384, (q2_at0 + a) * 64, rb * 128);
      bulk_commit_wait();
      flag_add(&g_flags[(F_QKV + rb) * FSTR]);
      TS(12);
      flag_wait(&g_flags[(F_QKV + rb) * FSTR], 11);
      if (rb > 0) flag_wait(&g_flags[(F_QKV + rb - 1) * FSTR], 11);
      fence_async();
      TS(13);
      uint32_t fb = bars + B_ATTFULL * 8;
      mbar_expect(fb, 128 * 160 + 2 * 142 * 160);
      tma_load3(stg, &maps.qkv_ldq, fb, 80 * j, rb * 64);
      tma_load3(stg + ATT_K_OFF, &maps.qkv_ldkv, fb, 640 + 80 * j, rb * 64 - 7);
      tma_load3(stg + ATT_V_OFF, &maps.qkv_ldkv, fb, 1280 + 80 * j, rb * 64 - 7);
      finish_reader();
    }
   }
  } else {
    asm volatile("setmaxnreg.inc.sync.aligned.u32 200;");
    const int wg = wgi - 1;
    int slot = 0, cnt = 0;
    if (tid == 128) TS(0);
    const int ct = tid - 128;
    uint8_t* const stp = sp + STG_OFF;
    const float* const sGp = reinterpret_cast<const float*>(sp + SG_OFF);
    auto nobg = [](int) {};
    if (!regular) {
      asm volatile("barrier.cluster.wait.acquire.aligned;" ::: "memory");
      for (int tl = 0; tl < 4; tl++) {
        float acc[32];
        tile_loop<64, 6, SLOTX>(acc, ring, bars + B_FULL1 * 8, bars + B_EMPTY1 * 8, slot, cnt, wg, lane, nobg);
        if (tl > 0) mbar_wait(bars + B_STGFREE * 8, (tl - 1) & 1);
        dump_tile<64>(acc, ring + STG_OFF, wg, warp, lane);
        fence_async_smem();
        named_bar(2, 256);
        if (tid == 128) mbar_arrive(bars + B_STGFULL * 8);
      }
    } else {
      uint4 bv[4];
#pragma unroll
      for (int a = 0; a < 4; a++) bv[a] = __ldg(reinterpret_cast<const uint4*>(b1 + min(w1_at0 + a, 26) * 64 + (ct & 7) * 8));
      {
        float acc[128];
        tile_loop<256, 4, SLOT1>(acc, ring, bars + B_FULL1 * 8, bars + B_EMPTY1 * 8, slot, cnt, wg, lane, nobg);
        if (tid == 128) TS(1);
        named_bar(2, 256);
        dump_tile<256>(acc, ring + STG_OFF, wg, warp, lane);
        fence_async_smem();
        named_bar(2, 256);
      }
      if (tid == 128) { mbar_arrive(bars + B_STGFULL * 8); TS(2); }
      asm volatile("barrier.cluster.wait.acquire.aligned;" ::: "memory");
      slot = 3; cnt = 0;
      {
        float acc[96];
        float omr[4];
        uint4 vn[2];
        tile_loop<192, 4, SLOT2>(acc, ring, bars + B_FULL2 * 8, bars + B_EMPTY2 * 8, slot, cnt, wg, lane, [&](int k) {
          if (k == 0) {
            mbar_wait(bars + B_GREADY * 8, 0);
#pragma unroll
            for (int i = 0; i < 4; i++) omr[i] = 1.f - sGp[(ct >> 3) + 32 * i];
            vn[0] = *mish_ptr(stp, 0, 0, ct); vn[1] = *mish_ptr(stp, 0, 1, ct);
          }
          if (k < nw1) {
            const uint4 b = k == 0 ? bv[0] : k == 1 ? bv[1] : k == 2 ? bv[2] : bv[3];
#pragma unroll 1
            for (int sl = 2 * k; sl < 2 * k + 2; sl++) {
              const uint4 v[2] = {vn[0], vn[1]};
              if (sl + 1 < 2 * nw1) { vn[0] = *mish_ptr(stp, sl + 1, 0, ct); vn[1] = *mish_ptr(stp, sl + 1, 1, ct); }
              mish_slice(stp, omr, b, v, sl, ct);
            }
            warp_done(bars + B_HDONE * 8, lane);
          }
        });
        if (tid == 128) TS(3);
        mbar_wait(bars + B_STGFREE * 8, 0);
        named_bar(2, 256);
        dump_tile<192>(acc, ring + STG_OFF, wg, warp, lane);
        fence_async_smem();
        named_bar(2, 256);
      }
      if (tid == 128) { mbar_arrive(bars + B_STGFULL * 8); TS(4); }

      const int g8 = lane >> 2, c4 = lane & 3;
      const int par = warp & 1, P0 = ((wg * 4 + warp) >> 1) * 16;
      const uint32_t stq = ring + STG_OFF + par * (64 * 160);
      const uint32_t stk = ring + STG_OFF + ATT_K_OFF + par * (71 * 160);
      const uint32_t stv = ring + STG_OFF + ATT_V_OFF + par * (71 * 160);
      int ast = 0;
      auto att_step = [&]() {
        if (tid == 128 && ast == 0) TS(22);
        const bool oddh = (ast & 1) != 0;
        const int hoffb = ast * 40 - (oddh ? 8 : 0);
        uint32_t qa[4], qb[2];
        {
          const uint32_t qrow = stq + (P0 + (lane & 7) + ((lane >> 3) & 1) * 8) * 160 + hoffb;
          ldsm4(qa, qrow + (lane >> 4) * 16);
          ldsm2(qb, qrow + 32);
          if (oddh) { if (c4 < 2) { qa[0] = 0u; qa[1] = 0u; } }
          else if (c4 >= 2) { qb[0] = 0u; qb[1] = 0u; }
        }
        const int chunk = min(lane >> 3, 2);
        float sfr[3][4];
#pragma unroll
        for (int n = 0; n < 3; n++) {
          uint32_t kb[4];
          ldsm4(kb, stk + min(P0 + 8 * n + (lane & 7), 70) * 160 + hoffb + chunk * 16);
          sfr[n][0] = sfr[n][1] = sfr[n][2] = sfr[n][3] = 0.f;
          mma16816(sfr[n], qa[0], qa[1], qa[2], qa[3], kb[0], kb[1]);
          mma16816(sfr[n], qb[0], qb[1], 0u, 0u, kb[2], 0u);
        }
        uint32_t vb[3][4];
#pragma unroll
        for (int d = 0; d < 3; d++) ldsm4t(vb[d], stv + min(P0 + 8 * chunk + (lane & 7), 70) * 160 + hoffb + d * 16);
        const float sc = 0.22360679774997896f * 1.4426950408889634f;
        const int tmin = 7 - (rb * 64 + P0);
        float mx0 = -3.0e38f, mx1 = -3.0e38f;
#pragma unroll
        for (int n = 0; n < 3; n++) {
#pragma unroll
          for (int e = 0; e < 2; e++) {
            const int t = 8 * n + 2 * c4 + e;
            sfr[n][e] = (t >= g8 && t <= g8 + 7 && t >= tmin) ? sfr[n][e] * sc : -3.0e38f;
            sfr[n][2 + e] = (t >= g8 + 8 && t <= g8 + 15 && t >= tmin) ? sfr[n][2 + e] * sc : -3.0e38f;
            mx0 = fmaxf(mx0, sfr[n][e]); mx1 = fmaxf(mx1, sfr[n][2 + e]);
          }
        }
        mx0 = fmaxf(mx0, __shfl_xor_sync(0xffffffffu, mx0, 1)); mx1 = fmaxf(mx1, __shfl_xor_sync(0xffffffffu, mx1, 1));
        mx0 = fmaxf(mx0, __shfl_xor_sync(0xffffffffu, mx0, 2)); mx1 = fmaxf(mx1, __shfl_xor_sync(0xffffffffu, mx1, 2));
        float s0 = 0.f, s1 = 0.f;
#pragma unroll
        for (int n = 0; n < 3; n++) {
#pragma unroll
          for (int e = 0; e < 2; e++) {
            sfr[n][e] = ex2f(sfr[n][e] - mx0); sfr[n][2 + e] = ex2f(sfr[n][2 + e] - mx1);
            s0 += sfr[n][e]; s1 += sfr[n][2 + e];
          }
        }
        s0 += __shfl_xor_sync(0xffffffffu, s0, 1); s1 += __shfl_xor_sync(0xffffffffu, s1, 1);
        s0 += __shfl_xor_sync(0xffffffffu, s0, 2); s1 += __shfl_xor_sync(0xffffffffu, s1, 2);
        const uint32_t p0 = pack_bf16(sfr[0][0], sfr[0][1]), p1 = pack_bf16(sfr[0][2], sfr[0][3]);
        const uint32_t p2 = pack_bf16(sfr[1][0], sfr[1][1]), p3 = pack_bf16(sfr[1][2], sfr[1][3]);
        const uint32_t p4 = pack_bf16(sfr[2][0], sfr[2][1]), p5 = pack_bf16(sfr[2][2], sfr[2][3]);
        const float f0 = sGp[2 * (P0 + g8) + par] * rcpf(s0), f1 = sGp[2 * (P0 + g8 + 8) + par] * rcpf(s1);
        float ofr[3][4];
#pragma unroll
        for (int d = 0; d < 3; d++) {
          ofr[d][0] = ofr[d][1] = ofr[d][2] = ofr[d][3] = 0.f;
          mma16816(ofr[d], p0, p1, p2, p3, vb[d][0], vb[d][1]);
          mma16816(ofr[d], p4, p5, 0u, 0u, vb[d][2], 0u);
        }
        __syncwarp();
        uint8_t* op = stp + par * (64 * 160) + (P0 + g8) * 160 + hoffb + c4 * 4;
#pragma unroll
        for (int d = 0; d < 3; d++) {
          const bool ok = oddh ? (d > 0 || c4 >= 2) : (d < 2 || c4 < 2);
          if (ok) {
            *reinterpret_cast<uint32_t*>(op + d * 16) = pack_bf16(ofr[d][0] * f0, ofr[d][1] * f0);
            *reinterpret_cast<uint32_t*>(op + 8 * 160 + d * 16) = pack_bf16(ofr[d][2] * f1, ofr[d][3] * f1);
          }
        }
        if (ast == 3) {
          warp_done(bars + B_ODONE * 8, lane);
          if (tid == 128) TS(26);
        }
        ast++;
      };
      const int nh = rank == 0 ? 14 : 13;
      float accA[64], accB[16];
      zero_acc(accA); zero_acc(accB);
      const uint64_t hoff = 1024 + ((nt & 1) ? 4 : 0);
      mainloop<4, SLOT2>(ring, bars + B_FULL2 * 8, bars + B_EMPTY2 * 8, slot, cnt, nh + 5, wg, lane, [&](uint64_t da, uint64_t db) {
#pragma unroll
        for (int kk = 0; kk < 4; kk++) {
          wgmma_n128(accA, da + kk * 2, db + kk * 128, 1);
          wgmma_n32(accB, da + kk * 2, db + hoff + kk * 128, 1);
        }
      }, [&](int k) {
        if (k == K_ATT) {
          mbar_wait(bars + B_ATTFULL * 8, 0);
          wg_wait<0>();
#pragma unroll 2
          for (int hh = 0; hh < 4; hh++) att_step();
        }
      });
      pin_acc(accA); pin_acc(accB);
      float acc[80];
#pragma unroll
      for (int i = 0; i < 64; i++) acc[i] = accA[i];
#pragma unroll
      for (int i = 0; i < 16; i++) acc[64 + i] = accB[i];
      const uint32_t peer = rank ^ 1;
      if (tid == 128) TS(5);
      mbar_wait_cl(bars + B_PEERFREE * 8, 0);
      const uint32_t rdst = mapa(ring + STG_OFF + ATT_K_OFF + ct * 16, peer);
      const uint32_t rbar = mapa(bars + B_PEERDATA * 8, peer);
      const bool odd = (nt & 1) != 0;
      float keep[40], snd[40];
#pragma unroll
      for (int i = 0; i < 10; i++) {
        const int be0 = i, be1 = 10 + i;
        const int bo0 = i < 4 ? 16 + i : i - 4, bo1 = 6 + i;
#pragma unroll
        for (int e = 0; e < 4; e++) {
          const float r0 = odd ? acc[4 * bo0 + e] : acc[4 * be0 + e];
          const float r1 = odd ? acc[4 * bo1 + e] : acc[4 * be1 + e];
          keep[4 * i + e] = rank == 0 ? r0 : r1;
          snd[4 * i + e] = rank == 0 ? r1 : r0;
        }
      }
#pragma unroll
      for (int i = 0; i < 10; i++)
        asm volatile("st.async.shared::cluster.mbarrier::complete_tx::bytes.v4.f32 [%0], {%1,%2,%3,%4}, [%5];"
                     ::"r"(rdst + i * 4096), "f"(snd[4 * i]), "f"(snd[4 * i + 1]), "f"(snd[4 * i + 2]), "f"(snd[4 * i + 3]), "r"(rbar) : "memory");
      mbar_wait_cl(bars + B_PEERDATA * 8, 0);
      if (tid == 128) TS(6);
      uint8_t* orow = sp + (wg * 64 + warp * 16 + (lane >> 2)) * 160 + (lane & 3) * 4;
#pragma unroll
      for (int i = 0; i < 10; i++) {
        const float4 v = *reinterpret_cast<const float4*>(stp + ATT_K_OFF + ct * 16 + i * 4096);
        *reinterpret_cast<uint32_t*>(orow + i * 16) = pack_bf16(v.x + keep[4 * i], v.y + keep[4 * i + 1]);
        *reinterpret_cast<uint32_t*>(orow + 8 * 160 + i * 16) = pack_bf16(v.z + keep[4 * i + 2], v.w + keep[4 * i + 3]);
      }
      fence_async_smem();
      named_bar(2, 256);
      if (tid == 128) {
        tma_store(&maps.out_st, ring, 160 * nt + 80 * rank, rb2 * 128);
        asm volatile("cp.async.bulk.commit_group;" ::: "memory");
        asm volatile("cp.async.bulk.wait_group.read 0;" ::: "memory");
      }
      if (tid == 128) TS(7);
    }
  }
}

typedef CUresult (*EncFn)(CUtensorMap*, CUtensorMapDataType, cuuint32_t, void*, const cuuint64_t*, const cuuint64_t*,
                          const cuuint32_t*, const cuuint32_t*, CUtensorMapInterleave, CUtensorMapSwizzle,
                          CUtensorMapL2promotion, CUtensorMapFloatOOBfill);

void make_map(EncFn enc, CUtensorMap* m, const void* p, int cols, int rows, int bc, int br, bool swz) {
  cuuint64_t d[2] = {(cuuint64_t)cols, (cuuint64_t)rows};
  cuuint64_t s[1] = {(cuuint64_t)cols * 2};
  cuuint32_t b[2] = {(cuuint32_t)bc, (cuuint32_t)br};
  cuuint32_t e[2] = {1, 1};
  enc(m, CU_TENSOR_MAP_DATA_TYPE_BFLOAT16, 2, const_cast<void*>(p), d, s, b, e, CU_TENSOR_MAP_INTERLEAVE_NONE,
      swz ? CU_TENSOR_MAP_SWIZZLE_128B : CU_TENSOR_MAP_SWIZZLE_NONE, CU_TENSOR_MAP_L2_PROMOTION_L2_128B,
      CU_TENSOR_MAP_FLOAT_OOB_FILL_NONE);
}

void make_map3(EncFn enc, CUtensorMap* m, const void* p, int cols, int rows, int bc, int bpairs) {
  cuuint64_t d[3] = {(cuuint64_t)cols, (cuuint64_t)rows / 2, 2};
  cuuint64_t s[2] = {(cuuint64_t)cols * 4, (cuuint64_t)cols * 2};
  cuuint32_t b[3] = {(cuuint32_t)bc, (cuuint32_t)bpairs, 2};
  cuuint32_t e[3] = {1, 1, 1};
  enc(m, CU_TENSOR_MAP_DATA_TYPE_BFLOAT16, 3, const_cast<void*>(p), d, s, b, e, CU_TENSOR_MAP_INTERLEAVE_NONE,
      CU_TENSOR_MAP_SWIZZLE_NONE, CU_TENSOR_MAP_L2_PROMOTION_L2_128B, CU_TENSOR_MAP_FLOAT_OOB_FILL_NONE);
}

}

extern "C" void kernel_launch(void* const* d_in, const int* in_sizes, int n_in, void* d_out, int out_size) {
  (void)in_sizes; (void)n_in; (void)out_size;
  static Maps maps;
  static const void* seen[9] = {nullptr};
  bool same = seen[8] == d_out;
  for (int i = 0; i < 8; i++) same = same && seen[i] == d_in[i];
  if (!same) {
    for (int i = 0; i < 8; i++) seen[i] = d_in[i];
    seen[8] = d_out;
    EncFn enc = nullptr;
    cudaDriverEntryPointQueryResult q;
    cudaGetDriverEntryPoint("cuTensorMapEncodeTiled", (void**)&enc, cudaEnableDefault, &q);
    void *ph, *po, *pq;
    cudaGetSymbolAddress(&ph, g_h);
    cudaGetSymbolAddress(&po, g_o);
    cudaGetSymbolAddress(&pq, g_qkv);
    make_map(enc, &maps.x, d_in[0], DM, SEQ, 64, 128, true);
    make_map(enc, &maps.wqkv, d_in[1], QKVN, DM, 64, 64, true);
    make_map(enc, &maps.wo, d_in[2], DM, DM, 64, 64, true);
    make_map(enc, &maps.w1, d_in[4], FF, DM, 64, 64, true);
    make_map(enc, &maps.w2, d_in[6], DM, FF, 64, 64, true);
    make_map(enc, &maps.h, ph, FF, SEQ, 64, 128, true);
    make_map(enc, &maps.o, po, DM, SEQ, 64, 128, true);
    make_map(enc, &maps.qkv_st, pq, QKVN, SEQ, 64, 128, true);
    make_map3(enc, &maps.qkv_ldq, pq, QKVN, SEQ, 80, 64);
    make_map3(enc, &maps.qkv_ldkv, pq, QKVN, SEQ, 80, 71);
    make_map3(enc, &maps.o_st, po, DM, SEQ, 80, 64);
    make_map(enc, &maps.out_st, d_out, DM, SEQ, 80, 128, false);
    cudaFuncSetAttribute(fused_kernel, cudaFuncAttributeMaxDynamicSharedMemorySize, SMEM_ALLOC);
  }
  fused_kernel<<<NCTAS, NTHREADS, SMEM_ALLOC>>>(maps, (const __nv_bfloat16*)d_in[5], (const __nv_bfloat16*)d_in[7],
                                               (const uint8_t*)d_in[1], (const uint8_t*)d_in[6], (const uint8_t*)d_in[2]);
}
```

```cpp
#include <cuda_runtime.h>
#include <cuda.h>
#include <cuda_bf16.h>
#include <stdint.h>

namespace {

constexpr int SEQ = 2048, DM = 640, FF = 1728, QKVN = 1920;
constexpr int NTHREADS = 384;
constexpr int NREG_CTAS = 128;
constexpr int NCTAS = 132;

#define K_ATT 7

constexpr int RING_BYTES = 163840;
constexpr int SLOT1 = 49152;
constexpr int SLOT2 = 40960;
constexpr int SLOTX = 24576;
constexpr int STG_OFF = RING_BYTES;
constexpr int STG_BYTES = 66048;
constexpr int ATT_K_OFF = 20480;
constexpr int ATT_V_OFF = 43264;
constexpr int MISC_OFF = STG_OFF + STG_BYTES;
constexpr int SG_OFF = MISC_OFF + 256;
constexpr int SMEM_USED = SG_OFF + 1024;
constexpr int SMEM_ALLOC = SMEM_USED + 1024;

enum { B_FULL1 = 0, B_EMPTY1 = 6, B_FULL2 = 12, B_EMPTY2 = 16,
       B_STGFULL = 20, B_GREADY = 21, B_ATTFULL = 22, B_PEERFREE = 23, B_PEERDATA = 24, B_HDONE = 25, B_ODONE = 26,
       B_STGFREE = 27, B_HD1 = 28, B_COUNT = 31 };

enum { F_H = 0, F_QKV = 16, F_O = 32, F_FIN = 48 };
constexpr int FSTR = 32;

__device__ __nv_bfloat16 g_h[SEQ * FF];
__device__ __nv_bfloat16 g_o[SEQ * DM];
__device__ __nv_bfloat16 g_qkv[SEQ * QKVN];
__device__ unsigned g_flags[64 * 32];

struct Maps { CUtensorMap x, wqkv, w1, w2, wo, h, o, qkv_st, qkv_ldq, qkv_ldkv, o_st, out_st; };

__device__ __forceinline__ uint32_t s2u(const void* p) { return (uint32_t)__cvta_generic_to_shared(p); }
__device__ __forceinline__ void mbar_init(uint32_t b, int c) { asm volatile("mbarrier.init.shared::cta.b64 [%0], %1;" ::"r"(b), "r"(c)); }
__device__ __forceinline__ void mbar_expect(uint32_t b, int bytes) { asm volatile("mbarrier.arrive.expect_tx.shared::cta.b64 _, [%0], %1;" ::"r"(b), "r"(bytes) : "memory"); }
__device__ __forceinline__ void mbar_arrive(uint32_t b) { asm volatile("mbarrier.arrive.shared::cta.b64 _, [%0];" ::"r"(b) : "memory"); }
__device__ __forceinline__ bool mbar_try(uint32_t b, int par) {
  uint32_t ok;
  asm volatile("{\n.reg .pred p;\nmbarrier.try_wait.parity.shared::cta.b64 p, [%1], %2;\nselp.u32 %0, 1, 0, p;\n}" : "=r"(ok) : "r"(b), "r"(par) : "memory");
  return ok != 0;
}
__device__ __forceinline__ bool mbar_test(uint32_t b, int par) {
  uint32_t ok;
  asm volatile("{\n.reg .pred p;\nmbarrier.test_wait.parity.shared::cta.b64 p, [%1], %2;\nselp.u32 %0, 1, 0, p;\n}" : "=r"(ok) : "r"(b), "r"(par) : "memory");
  return ok != 0;
}
#define TRAP(c, e) __trap()
__device__ __forceinline__ void mbar_wait(uint32_t b, int par) {
  uint32_t n = 0;
  while (!mbar_try(b, par)) { if (++n > (1u << 22)) TRAP(1, (b & 255) / 8 + 1000 * par); }
}
__device__ __forceinline__ bool mbar_try_cl(uint32_t b, int par) {
  uint32_t ok;
  asm volatile("{\n.reg .pred p;\nmbarrier.try_wait.parity.acquire.cluster.shared::cta.b64 p, [%1], %2;\nselp.u32 %0, 1, 0, p;\n}" : "=r"(ok) : "r"(b), "r"(par) : "memory");
  return ok != 0;
}
__device__ __forceinline__ void mbar_wait_cl(uint32_t b, int par) {
  uint32_t n = 0;
  while (!mbar_try_cl(b, par)) { if (++n > (1u << 22)) TRAP(2, (b & 255) / 8); }
}
__device__ __forceinline__ uint32_t mapa(uint32_t a, uint32_t cta) { uint32_t r; asm volatile("mapa.shared::cluster.u32 %0, %1, %2;" : "=r"(r) : "r"(a), "r"(cta)); return r; }
__device__ __forceinline__ void mbar_arrive_cl(uint32_t remote) { asm volatile("mbarrier.arrive.release.cluster.shared::cluster.b64 _, [%0];" ::"r"(remote) : "memory"); }
__device__ __forceinline__ void tma_load(uint32_t dst, const CUtensorMap* m, uint32_t bar, int c0, int c1) {
  asm volatile("cp.async.bulk.tensor.2d.shared::cluster.global.mbarrier::complete_tx::bytes [%0], [%1, {%3,%4}], [%2];" ::"r"(dst), "l"(m), "r"(bar), "r"(c0), "r"(c1) : "memory");
}
__device__ __forceinline__ void tma_load3(uint32_t dst, const CUtensorMap* m, uint32_t bar, int c0, int c1) {
  asm volatile("cp.async.bulk.tensor.3d.shared::cluster.global.mbarrier::complete_tx::bytes [%0], [%1, {%3,%4,%5}], [%2];" ::"r"(dst), "l"(m), "r"(bar), "r"(c0), "r"(c1), "r"(0) : "memory");
}
__device__ __forceinline__ void tma_store3(const CUtensorMap* m, uint32_t src, int c0, int c1) {
  asm volatile("cp.async.bulk.tensor.3d.global.shared::cta.bulk_group [%0, {%2,%3,%4}], [%1];" ::"l"(m), "r"(src), "r"(c0), "r"(c1), "r"(0) : "memory");
}
__device__ __forceinline__ void tma_store(const CUtensorMap* m, uint32_t src, int c0, int c1) {
  asm volatile("cp.async.bulk.tensor.2d.global.shared::cta.bulk_group [%0, {%2,%3}], [%1];" ::"l"(m), "r"(src), "r"(c0), "r"(c1) : "memory");
}
__device__ __forceinline__ void fence_async() { asm volatile("fence.proxy.async.global;" ::: "memory"); }
__device__ __forceinline__ void fence_async_smem() { asm volatile("fence.proxy.async.shared::cta;" ::: "memory"); }
__device__ __forceinline__ void wg_fence() { asm volatile("wgmma.fence.sync.aligned;" ::: "memory"); }
__device__ __forceinline__ void wg_commit() { asm volatile("wgmma.commit_group.sync.aligned;" ::: "memory"); }
template <int N> __device__ __forceinline__ void wg_wait() { asm volatile("wgmma.wait_group.sync.aligned %0;" ::"n"(N) : "memory"); }
__device__ __forceinline__ void named_bar(int id, int n) { asm volatile("bar.sync %0, %1;" ::"r"(id), "r"(n) : "memory"); }
__device__ __forceinline__ unsigned ld_rlx(const unsigned* p) { unsigned v; asm volatile("ld.relaxed.gpu.global.u32 %0, [%1];" : "=r"(v) : "l"(p) : "memory"); return v; }
__device__ __forceinline__ void flag_add(unsigned* p) { asm volatile("red.relaxed.gpu.global.add.u32 [%0], 1;" ::"l"(p) : "memory"); }
__device__ __forceinline__ void flag_wait(const unsigned* p, unsigned target) {
  uint32_t n = 0;
  while (ld_rlx(p) < target) { __nanosleep(32); if (++n > (1u << 20)) TRAP(3, (unsigned)(p - g_flags)); }
}
__device__ __forceinline__ void bulk_commit_wait() {
  asm volatile("cp.async.bulk.commit_group;" ::: "memory");
  asm volatile("cp.async.bulk.wait_group 0;" ::: "memory");
}
__device__ __forceinline__ void finish_reader() {
  unsigned old = atomicAdd(&g_flags[F_FIN * FSTR], 1u);
  if (old == 2 * NREG_CTAS - 1) {
    for (int i = 0; i <= F_FIN; i++) g_flags[i * FSTR] = 0;
  }
}
#define TS(i)
#define TR()
__device__ __forceinline__ uint32_t pack_bf16(float a, float b) { __nv_bfloat162 t = __floats2bfloat162_rn(a, b); return *reinterpret_cast<uint32_t*>(&t); }
__device__ __forceinline__ float bf_lo(uint32_t v) { return __uint_as_float(v << 16); }
__device__ __forceinline__ float bf_hi(uint32_t v) { return __uint_as_float(v & 0xffff0000u); }

__device__ __forceinline__ uint64_t desc_a(uint32_t a) { return (uint64_t)((a & 0x3FFFF) >> 4) | (1ull << 16) | (64ull << 32) | (1ull << 62); }
__device__ __forceinline__ uint64_t desc_b(uint32_t a) { return (uint64_t)((a & 0x3FFFF) >> 4) | (512ull << 16) | (64ull << 32) | (1ull << 62); }

__device__ __forceinline__ void wgmma_n256(float (&d)[128], uint64_t da, uint64_t db, int sc) {
  asm volatile("{\n.reg .pred p;\nsetp.ne.b32 p, %130, 0;\n"
    "wgmma.mma_async.sync.aligned.m64n256k16.f32.bf16.bf16 {%0, %1, %2, %3, %4, %5, %6, %7, %8, %9, %10, %11, %12, %13, %14, %15, %16, %17, %18, %19, %20, %21, %22, %23, %24, %25, %26, %27, %28, %29, %30, %31, %32, %33, %34, %35, %36, %37, %38, %39, %40, %41, %42, %43, %44, %45, %46, %47, %48, %49, %50, %51, %52, %53, %54, %55, %56, %57, %58, %59, %60, %61, %62, %63, %64, %65, %66, %67, %68, %69, %70, %71, %72, %73, %74, %75, %76, %77, %78, %79, %80, %81, %82, %83, %84, %85, %86, %87, %88, %89, %90, %91, %92, %93, %94, %95, %96, %97, %98, %99, %100, %101, %102, %103, %104, %105, %106, %107, %108, %109, %110, %111, %112, %113, %114, %115, %116, %117, %118, %119, %120, %121, %122, %123, %124, %125, %126, %127}, %128, %129, p, 1, 1, 0, 1;\n}\n"
    : "+f"(d[0]), "+f"(d[1]), "+f"(d[2]), "+f"(d[3]), "+f"(d[4]), "+f"(d[5]), "+f"(d[6]), "+f"(d[7]), "+f"(d[8]), "+f"(d[9]), "+f"(d[10]), "+f"(d[11]), "+f"(d[12]), "+f"(d[13]), "+f"(d[14]), "+f"(d[15]), "+f"(d[16]), "+f"(d[17]), "+f"(d[18]), "+f"(d[19]), "+f"(d[20]), "+f"(d[21]), "+f"(d[22]), "+f"(d[23]), "+f"(d[24]), "+f"(d[25]), "+f"(d[26]), "+f"(d[27]), "+f"(d[28]), "+f"(d[29]), "+f"(d[30]), "+f"(d[31]), "+f"(d[32]), "+f"(d[33]), "+f"(d[34]), "+f"(d[35]), "+f"(d[36]), "+f"(d[37]), "+f"(d[38]), "+f"(d[39]), "+f"(d[40]), "+f"(d[41]), "+f"(d[42]), "+f"(d[43]), "+f"(d[44]), "+f"(d[45]), "+f"(d[46]), "+f"(d[47]), "+f"(d[48]), "+f"(d[49]), "+f"(d[50]), "+f"(d[51]), "+f"(d[52]), "+f"(d[53]), "+f"(d[54]), "+f"(d[55]), "+f"(d[56]), "+f"(d[57]), "+f"(d[58]), "+f"(d[59]), "+f"(d[60]), "+f"(d[61]), "+f"(d[62]), "+f"(d[63]), "+f"(d[64]), "+f"(d[65]), "+f"(d[66]), "+f"(d[67]), "+f"(d[68]), "+f"(d[69]), "+f"(d[70]), "+f"(d[71]), "+f"(d[72]), "+f"(d[73]), "+f"(d[74]), "+f"(d[75]), "+f"(d[76]), "+f"(d[77]), "+f"(d[78]), "+f"(d[79]), "+f"(d[80]), "+f"(d[81]), "+f"(d[82]), "+f"(d[83]), "+f"(d[84]), "+f"(d[85]), "+f"(d[86]), "+f"(d[87]), "+f"(d[88]), "+f"(d[89]), "+f"(d[90]), "+f"(d[91]), "+f"(d[92]), "+f"(d[93]), "+f"(d[94]), "+f"(d[95]), "+f"(d[96]), "+f"(d[97]), "+f"(d[98]), "+f"(d[99]), "+f"(d[100]), "+f"(d[101]), "+f"(d[102]), "+f"(d[103]), "+f"(d[104]), "+f"(d[105]), "+f"(d[106]), "+f"(d[107]), "+f"(d[108]), "+f"(d[109]), "+f"(d[110]), "+f"(d[111]), "+f"(d[112]), "+f"(d[113]), "+f"(d[114]), "+f"(d[115]), "+f"(d[116]), "+f"(d[117]), "+f"(d[118]), "+f"(d[119]), "+f"(d[120]), "+f"(d[121]), "+f"(d[122]), "+f"(d[123]), "+f"(d[124]), "+f"(d[125]), "+f"(d[126]), "+f"(d[127])
    : "l"(da), "l"(db), "r"(sc));
}
__device__ __forceinline__ void wgmma_n192(float (&d)[96], uint64_t da, uint64_t db, int sc) {
  asm volatile("{\n.reg .pred p;\nsetp.ne.b32 p, %98, 0;\n"
    "wgmma.mma_async.sync.aligned.m64n192k16.f32.bf16.bf16 {%0, %1, %2, %3, %4, %5, %6, %7, %8, %9, %10, %11, %12, %13, %14, %15, %16, %17, %18, %19, %20, %21, %22, %23, %24, %25, %26, %27, %28, %29, %30, %31, %32, %33, %34, %35, %36, %37, %38, %39, %40, %41, %42, %43, %44, %45, %46, %47, %48, %49, %50, %51, %52, %53, %54, %55, %56, %57, %58, %59, %60, %61, %62, %63, %64, %65, %66, %67, %68, %69, %70, %71, %72, %73, %74, %75, %76, %77, %78, %79, %80, %81, %82, %83, %84, %85, %86, %87, %88, %89, %90, %91, %92, %93, %94, %95}, %96, %97, p, 1, 1, 0, 1;\n}\n"
    : "+f"(d[0]), "+f"(d[1]), "+f"(d[2]), "+f"(d[3]), "+f"(d[4]), "+f"(d[5]), "+f"(d[6]), "+f"(d[7]), "+f"(d[8]), "+f"(d[9]), "+f"(d[10]), "+f"(d[11]), "+f"(d[12]), "+f"(d[13]), "+f"(d[14]), "+f"(d[15]), "+f"(d[16]), "+f"(d[17]), "+f"(d[18]), "+f"(d[19]), "+f"(d[20]), "+f"(d[21]), "+f"(d[22]), "+f"(d[23]), "+f"(d[24]), "+f"(d[25]), "+f"(d[26]), "+f"(d[27]), "+f"(d[28]), "+f"(d[29]), "+f"(d[30]), "+f"(d[31]), "+f"(d[32]), "+f"(d[33]), "+f"(d[34]), "+f"(d[35]), "+f"(d[36]), "+f"(d[37]), "+f"(d[38]), "+f"(d[39]), "+f"(d[40]), "+f"(d[41]), "+f"(d[42]), "+f"(d[43]), "+f"(d[44]), "+f"(d[45]), "+f"(d[46]), "+f"(d[47]), "+f"(d[48]), "+f"(d[49]), "+f"(d[50]), "+f"(d[51]), "+f"(d[52]), "+f"(d[53]), "+f"(d[54]), "+f"(d[55]), "+f"(d[56]), "+f"(d[57]), "+f"(d[58]), "+f"(d[59]), "+f"(d[60]), "+f"(d[61]), "+f"(d[62]), "+f"(d[63]), "+f"(d[64]), "+f"(d[65]), "+f"(d[66]), "+f"(d[67]), "+f"(d[68]), "+f"(d[69]), "+f"(d[70]), "+f"(d[71]), "+f"(d[72]), "+f"(d[73]), "+f"(d[74]), "+f"(d[75]), "+f"(d[76]), "+f"(d[77]), "+f"(d[78]), "+f"(d[79]), "+f"(d[80]), "+f"(d[81]), "+f"(d[82]), "+f"(d[83]), "+f"(d[84]), "+f"(d[85]), "+f"(d[86]), "+f"(d[87]), "+f"(d[88]), "+f"(d[89]), "+f"(d[90]), "+f"(d[91]), "+f"(d[92]), "+f"(d[93]), "+f"(d[94]), "+f"(d[95])
    : "l"(da), "l"(db), "r"(sc));
}
__device__ __forceinline__ void wgmma_n160(float (&d)[80], uint64_t da, uint64_t db, int sc) {
  asm volatile("{\n.reg .pred p;\nsetp.ne.b32 p, %82, 0;\n"
    "wgmma.mma_async.sync.aligned.m64n160k16.f32.bf16.bf16 {%0, %1, %2, %3, %4, %5, %6, %7, %8, %9, %10, %11, %12, %13, %14, %15, %16, %17, %18, %19, %20, %21, %22, %23, %24, %25, %26, %27, %28, %29, %30, %31, %32, %33, %34, %35, %36, %37, %38, %39, %40, %41, %42, %43, %44, %45, %46, %47, %48, %49, %50, %51, %52, %53, %54, %55, %56, %57, %58, %59, %60, %61, %62, %63, %64, %65, %66, %67, %68, %69, %70, %71, %72, %73, %74, %75, %76, %77, %78, %79}, %80, %81, p, 1, 1, 0, 1;\n}\n"
    : "+f"(d[0]), "+f"(d[1]), "+f"(d[2]), "+f"(d[3]), "+f"(d[4]), "+f"(d[5]), "+f"(d[6]), "+f"(d[7]), "+f"(d[8]), "+f"(d[9]), "+f"(d[10]), "+f"(d[11]), "+f"(d[12]), "+f"(d[13]), "+f"(d[14]), "+f"(d[15]), "+f"(d[16]), "+f"(d[17]), "+f"(d[18]), "+f"(d[19]), "+f"(d[20]), "+f"(d[21]), "+f"(d[22]), "+f"(d[23]), "+f"(d[24]), "+f"(d[25]), "+f"(d[26]), "+f"(d[27]), "+f"(d[28]), "+f"(d[29]), "+f"(d[30]), "+f"(d[31]), "+f"(d[32]), "+f"(d[33]), "+f"(d[34]), "+f"(d[35]), "+f"(d[36]), "+f"(d[37]), "+f"(d[38]), "+f"(d[39]), "+f"(d[40]), "+f"(d[41]), "+f"(d[42]), "+f"(d[43]), "+f"(d[44]), "+f"(d[45]), "+f"(d[46]), "+f"(d[47]), "+f"(d[48]), "+f"(d[49]), "+f"(d[50]), "+f"(d[51]), "+f"(d[52]), "+f"(d[53]), "+f"(d[54]), "+f"(d[55]), "+f"(d[56]), "+f"(d[57]), "+f"(d[58]), "+f"(d[59]), "+f"(d[60]), "+f"(d[61]), "+f"(d[62]), "+f"(d[63]), "+f"(d[64]), "+f"(d[65]), "+f"(d[66]), "+f"(d[67]), "+f"(d[68]), "+f"(d[69]), "+f"(d[70]), "+f"(d[71]), "+f"(d[72]), "+f"(d[73]), "+f"(d[74]), "+f"(d[75]), "+f"(d[76]), "+f"(d[77]), "+f"(d[78]), "+f"(d[79])
    : "l"(da), "l"(db), "r"(sc));
}
__device__ __forceinline__ void wgmma_n128(float (&d)[64], uint64_t da, uint64_t db, int sc) {
  asm volatile("{\n.reg .pred p;\nsetp.ne.b32 p, %66, 0;\n"
    "wgmma.mma_async.sync.aligned.m64n128k16.f32.bf16.bf16 {%0, %1, %2, %3, %4, %5, %6, %7, %8, %9, %10, %11, %12, %13, %14, %15, %16, %17, %18, %19, %20, %21, %22, %23, %24, %25, %26, %27, %28, %29, %30, %31, %32, %33, %34, %35, %36, %37, %38, %39, %40, %41, %42, %43, %44, %45, %46, %47, %48, %49, %50, %51, %52, %53, %54, %55, %56, %57, %58, %59, %60, %61, %62, %63}, %64, %65, p, 1, 1, 0, 1;\n}\n"
    : "+f"(d[0]), "+f"(d[1]), "+f"(d[2]), "+f"(d[3]), "+f"(d[4]), "+f"(d[5]), "+f"(d[6]), "+f"(d[7]), "+f"(d[8]), "+f"(d[9]), "+f"(d[10]), "+f"(d[11]), "+f"(d[12]), "+f"(d[13]), "+f"(d[14]), "+f"(d[15]), "+f"(d[16]), "+f"(d[17]), "+f"(d[18]), "+f"(d[19]), "+f"(d[20]), "+f"(d[21]), "+f"(d[22]), "+f"(d[23]), "+f"(d[24]), "+f"(d[25]), "+f"(d[26]), "+f"(d[27]), "+f"(d[28]), "+f"(d[29]), "+f"(d[30]), "+f"(d[31]), "+f"(d[32]), "+f"(d[33]), "+f"(d[34]), "+f"(d[35]), "+f"(d[36]), "+f"(d[37]), "+f"(d[38]), "+f"(d[39]), "+f"(d[40]), "+f"(d[41]), "+f"(d[42]), "+f"(d[43]), "+f"(d[44]), "+f"(d[45]), "+f"(d[46]), "+f"(d[47]), "+f"(d[48]), "+f"(d[49]), "+f"(d[50]), "+f"(d[51]), "+f"(d[52]), "+f"(d[53]), "+f"(d[54]), "+f"(d[55]), "+f"(d[56]), "+f"(d[57]), "+f"(d[58]), "+f"(d[59]), "+f"(d[60]), "+f"(d[61]), "+f"(d[62]), "+f"(d[63])
    : "l"(da), "l"(db), "r"(sc));
}
__device__ __forceinline__ void wgmma_n64(float (&d)[32], uint64_t da, uint64_t db, int sc) {
  asm volatile("{\n.reg .pred p;\nsetp.ne.b32 p, %34, 0;\n"
    "wgmma.mma_async.sync.aligned.m64n64k16.f32.bf16.bf16 {%0, %1, %2, %3, %4, %5, %6, %7, %8, %9, %10, %11, %12, %13, %14, %15, %16, %17, %18, %19, %20, %21, %22, %23, %24, %25, %26, %27, %28, %29, %30, %31}, %32, %33, p, 1, 1, 0, 1;\n}\n"
    : "+f"(d[0]), "+f"(d[1]), "+f"(d[2]), "+f"(d[3]), "+f"(d[4]), "+f"(d[5]), "+f"(d[6]), "+f"(d[7]), "+f"(d[8]), "+f"(d[9]), "+f"(d[10]), "+f"(d[11]), "+f"(d[12]), "+f"(d[13]), "+f"(d[14]), "+f"(d[15]), "+f"(d[16]), "+f"(d[17]), "+f"(d[18]), "+f"(d[19]), "+f"(d[20]), "+f"(d[21]), "+f"(d[22]), "+f"(d[23]), "+f"(d[24]), "+f"(d[25]), "+f"(d[26]), "+f"(d[27]), "+f"(d[28]), "+f"(d[29]), "+f"(d[30]), "+f"(d[31])
    : "l"(da), "l"(db), "r"(sc));
}
__device__ __forceinline__ void wgmma_n32(float (&d)[16], uint64_t da, uint64_t db, int sc) {
  asm volatile("{\n.reg .pred p;\nsetp.ne.b32 p, %18, 0;\n"
    "wgmma.mma_async.sync.aligned.m64n32k16.f32.bf16.bf16 {%0, %1, %2, %3, %4, %5, %6, %7, %8, %9, %10, %11, %12, %13, %14, %15}, %16, %17, p, 1, 1, 0, 1;\n}\n"
    : "+f"(d[0]), "+f"(d[1]), "+f"(d[2]), "+f"(d[3]), "+f"(d[4]), "+f"(d[5]), "+f"(d[6]), "+f"(d[7]), "+f"(d[8]), "+f"(d[9]), "+f"(d[10]), "+f"(d[11]), "+f"(d[12]), "+f"(d[13]), "+f"(d[14]), "+f"(d[15])
    : "l"(da), "l"(db), "r"(sc));
}

template <int N> struct MMA;
template <> struct MMA<256> { static __device__ __forceinline__ void run(float (&d)[128], uint64_t a, uint64_t b, int s) { wgmma_n256(d, a, b, s); } };
template <> struct MMA<192> { static __device__ __forceinline__ void run(float (&d)[96], uint64_t a, uint64_t b, int s) { wgmma_n192(d, a, b, s); } };
template <> struct MMA<160> { static __device__ __forceinline__ void run(float (&d)[80], uint64_t a, uint64_t b, int s) { wgmma_n160(d, a, b, s); } };
template <> struct MMA<64>  { static __device__ __forceinline__ void run(float (&d)[32], uint64_t a, uint64_t b, int s) { wgmma_n64(d, a, b, s); } };

template <int NS, int SLOTB, class ISSUE, class BG>
__device__ __forceinline__ void mainloop(uint32_t ring, uint32_t fullb, uint32_t emptyb, int& slot, int& cnt, int nk,
                                         int wg, int lane, ISSUE&& issue, BG&& bg) {
  int prev = -1;
  for (int k = 0; k < nk; k++) {
    if (!mbar_test(fullb + slot * 8, (cnt / NS) & 1)) {
      if (prev >= 0) {
        wg_wait<0>();
        if (lane == 0) mbar_arrive(emptyb + prev * 8);
        prev = -1;
      }
      mbar_wait(fullb + slot * 8, (cnt / NS) & 1);
    }
    uint32_t base = ring + slot * SLOTB;
    TR();
    wg_fence();
    issue(desc_a(base + wg * 8192), desc_b(base + 16384));
    wg_commit();
    wg_wait<1>();
    if (prev >= 0 && lane == 0) mbar_arrive(emptyb + prev * 8);
    bg(k);
    prev = slot;
    cnt++;
    if (++slot == NS) slot = 0;
  }
  wg_wait<0>();
  if (lane == 0) mbar_arrive(emptyb + prev * 8);
}
template <int R> __device__ __forceinline__ void zero_acc(float (&a)[R]) {
#pragma unroll
  for (int i = 0; i < R; i++) a[i] = 0.f;
}
template <int R> __device__ __forceinline__ void pin_acc(float (&a)[R]) {
#pragma unroll
  for (int i = 0; i < R; i++) asm volatile("" : "+f"(a[i])::"memory");
}
template <int N, int NS, int SLOTB, class BG>
__device__ __forceinline__ void tile_loop(float (&acc)[N / 2], uint32_t ring, uint32_t fullb, uint32_t emptyb,
                                          int& slot, int& cnt, int wg, int lane, BG&& bg) {
  zero_acc(acc);
  mainloop<NS, SLOTB>(ring, fullb, emptyb, slot, cnt, 10, wg, lane, [&](uint64_t da, uint64_t db) {
#pragma unroll
    for (int kk = 0; kk < 4; kk++) MMA<N>::run(acc, da + kk * 2, db + kk * 128, 1);
  }, bg);
  pin_acc(acc);
}

template <int N>
__device__ __forceinline__ void dump_tile(float (&acc)[N / 2], uint32_t stg, int wg, int warp, int lane) {
  int row = wg * 64 + warp * 16 + (lane & 7) + ((lane >> 3) & 1) * 8;
  uint32_t rbase = stg + row * 128;
  int csel = lane >> 4;
#pragma unroll
  for (int jb = 0; jb < N / 8; jb += 2) {
    uint32_t r0 = pack_bf16(acc[4 * jb + 0], acc[4 * jb + 1]);
    uint32_t r1 = pack_bf16(acc[4 * jb + 2], acc[4 * jb + 3]);
    uint32_t r2 = pack_bf16(acc[4 * jb + 4], acc[4 * jb + 5]);
    uint32_t r3 = pack_bf16(acc[4 * jb + 6], acc[4 * jb + 7]);
    int cb = jb + csel;
    uint32_t addr = rbase + (cb >> 3) * 16384 + (((cb & 7) ^ (row & 7)) << 4);
    asm volatile("stmatrix.sync.aligned.m8n8.x4.shared.b16 [%0], {%1,%2,%3,%4};" ::"r"(addr), "r"(r0), "r"(r1), "r"(r2), "r"(r3) : "memory");
  }
}

__device__ __forceinline__ float ex2f(float x) { float y; asm("ex2.approx.ftz.f32 %0, %1;" : "=f"(y) : "f"(x)); return y; }
__device__ __forceinline__ float rcpf(float x) { float y; asm("rcp.approx.ftz.f32 %0, %1;" : "=f"(y) : "f"(x)); return y; }

__device__ __forceinline__ float mish_f(float x, float om, float om2) {
  float e = ex2f(x * 1.4426950408889634f);
  float r = rcpf(fmaf(e, e + 2.f, 2.f));
  return fmaf(x * om2, r, x * om);
}

__device__ __forceinline__ void mma16816(float (&c)[4], uint32_t a0, uint32_t a1, uint32_t a2, uint32_t a3, uint32_t b0, uint32_t b1) {
  asm volatile("mma.sync.aligned.m16n8k16.row.col.f32.bf16.bf16.f32 {%0,%1,%2,%3}, {%4,%5,%6,%7}, {%8,%9}, {%0,%1,%2,%3};"
               : "+f"(c[0]), "+f"(c[1]), "+f"(c[2]), "+f"(c[3]) : "r"(a0), "r"(a1), "r"(a2), "r"(a3), "r"(b0), "r"(b1));
}

__device__ __forceinline__ void ldsm4(uint32_t (&r)[4], uint32_t a) {
  asm volatile("ldmatrix.sync.aligned.m8n8.x4.shared.b16 {%0,%1,%2,%3}, [%4];" : "=r"(r[0]), "=r"(r[1]), "=r"(r[2]), "=r"(r[3]) : "r"(a) : "memory");
}
__device__ __forceinline__ void ldsm4t(uint32_t (&r)[4], uint32_t a) {
  asm volatile("ldmatrix.sync.aligned.m8n8.x4.trans.shared.b16 {%0,%1,%2,%3}, [%4];" : "=r"(r[0]), "=r"(r[1]), "=r"(r[2]), "=r"(r[3]) : "r"(a) : "memory");
}
__device__ __forceinline__ void ldsm2(uint32_t (&r)[2], uint32_t a) {
  asm volatile("ldmatrix.sync.aligned.m8n8.x2.shared.b16 {%0,%1}, [%2];" : "=r"(r[0]), "=r"(r[1]) : "r"(a) : "memory");
}

__device__ __forceinline__ uint4* mish_ptr(uint8_t* stp, int s, int i, int ct) {
  const int row = (ct >> 3) + 64 * (s & 1) + 32 * i;
  return reinterpret_cast<uint4*>(stp + (s >> 1) * 16384 + row * 128 + (((ct & 7) ^ (row & 7)) << 4));
}
__device__ __forceinline__ void mish_slice(uint8_t* stp, const float (&omr)[4], const uint4 bv, const uint4 (&v)[2], int s, int ct) {
  const float bb[8] = {bf_lo(bv.x), bf_hi(bv.x), bf_lo(bv.y), bf_hi(bv.y), bf_lo(bv.z), bf_hi(bv.z), bf_lo(bv.w), bf_hi(bv.w)};
#pragma unroll
  for (int i = 0; i < 2; i++) {
    const float om = (s & 1) ? omr[2 + i] : omr[i], om2 = -2.f * om;
    uint4 o;
    o.x = pack_bf16(mish_f(bf_lo(v[i].x) + bb[0], om, om2), mish_f(bf_hi(v[i].x) + bb[1], om, om2));
    o.y = pack_bf16(mish_f(bf_lo(v[i].y) + bb[2], om, om2), mish_f(bf_hi(v[i].y) + bb[3], om, om2));
    o.z = pack_bf16(mish_f(bf_lo(v[i].z) + bb[4], om, om2), mish_f(bf_hi(v[i].z) + bb[5], om, om2));
    o.w = pack_bf16(mish_f(bf_lo(v[i].w) + bb[6], om, om2), mish_f(bf_hi(v[i].w) + bb[7], om, om2));
    *mish_ptr(stp, s, i, ct) = o;
  }
}

__device__ __forceinline__ void warp_done(uint32_t bar, int lane) {
  fence_async_smem();
  __syncwarp();
  if (lane == 0) mbar_arrive(bar);
}

__global__ void __cluster_dims__(2, 1, 1) __launch_bounds__(NTHREADS, 1)
fused_kernel(const __grid_constant__ Maps maps, const __nv_bfloat16* __restrict__ b1,
             const __nv_bfloat16* __restrict__ gate_w, const uint8_t* __restrict__ wqkv_raw,
             const uint8_t* __restrict__ w2_raw, const uint8_t* __restrict__ wo_raw) {
  extern __shared__ uint8_t smem_raw[];
  const uint32_t ring = (s2u(smem_raw) + 1023) & ~1023u;
  const uint32_t bars = ring + MISC_OFF;
  uint8_t* const sp = smem_raw + (ring - s2u(smem_raw));
  const int tid = threadIdx.x, wgi = tid >> 7, warp = (tid >> 5) & 3, lane = tid & 31;
  const int cta = blockIdx.x;
  const bool regular = cta < NREG_CTAS;
  const int rb = cta & 15, j = cta >> 4;
  const int nw1 = j < 6 ? 4 : (j == 6 ? 3 : 0);
  const int w1_at0 = 4 * j;
  const int q1_at0 = j == 6 ? 0 : 1;
  const int q2_at0 = 5 + 3 * j;
  const int xrb = (cta - NREG_CTAS) * 4;
  const int rank = cta & 1, pr = cta >> 1;
  const int rb2 = pr & 15, nt = pr >> 4;

  if (tid == 0) {
    for (int i = 0; i < 6; i++) { mbar_init(bars + (B_FULL1 + i) * 8, 1); mbar_init(bars + (B_EMPTY1 + i) * 8, regular ? 11 : 8); }
    for (int i = 0; i < 4; i++) { mbar_init(bars + (B_FULL2 + i) * 8, 1); mbar_init(bars + (B_EMPTY2 + i) * 8, 8); }
    mbar_init(bars + B_STGFULL * 8, 1);
    mbar_init(bars + B_STGFREE * 8, regular ? 2 : 1);
    mbar_init(bars + B_GREADY * 8, 3);
    mbar_init(bars + B_ATTFULL * 8, 1);
    mbar_init(bars + B_PEERFREE * 8, 1);
    mbar_init(bars + B_PEERDATA * 8, 1);
    mbar_init(bars + B_HDONE * 8, 8);
    for (int i = 0; i < 3; i++) mbar_init(bars + (B_HD1 + i) * 8, 8);
    mbar_init(bars + B_ODONE * 8, 8);
    mbar_expect(bars + B_PEERDATA * 8, 40960);
    asm volatile("fence.mbarrier_init.release.cluster;" ::: "memory");
  }
  if (tid == 32) {
    const CUtensorMap* mp = &maps.x;
    for (int i = 0; i < 12; i++) asm volatile("prefetch.tensormap [%0];" ::"l"(mp + i) : "memory");
  }
  if (tid == 64 && regular) {
    asm volatile("cp.async.bulk.prefetch.L2.global [%0], %1;" ::"l"(wqkv_raw + cta * 19200), "r"(19200) : "memory");
    asm volatile("cp.async.bulk.prefetch.L2.global [%0], %1;" ::"l"(w2_raw + cta * 17280), "r"(17280) : "memory");
    asm volatile("cp.async.bulk.prefetch.L2.global [%0], %1;" ::"l"(wo_raw + cta * 6400), "r"(6400) : "memory");
  }
  __syncthreads();
  asm volatile("barrier.cluster.arrive.release.aligned;" ::: "memory");

  if (wgi == 0) {
   asm volatile("setmaxnreg.dec.sync.aligned.u32 104;");
   const uint32_t stg = ring + STG_OFF;
   if (tid < 32) {
    if (tid == 0) {
      if (!regular) {
        int slot = 0;
        for (int i = 0; i < 40; i++) {
          mbar_wait(bars + (B_EMPTY1 + slot) * 8, ((i / 6) & 1) ^ 1);
          uint32_t base = ring + slot * SLOTX, fb = bars + (B_FULL1 + slot) * 8;
          const int t = i / 10, k = i - t * 10;
          mbar_expect(fb, SLOTX);
          tma_load(base, &maps.x, fb, k * 64, (xrb + t) * 128);
          tma_load(base + 16384, &maps.wqkv, fb, 29 * 64, k * 64);
          if (++slot == 6) slot = 0;
        }
      } else {
        for (int k = 0; k < 10; k++) {
          const int slot = k & 3;
          mbar_wait(bars + (B_EMPTY1 + slot) * 8, ((k >> 2) & 1) ^ 1);
          uint32_t base = ring + slot * SLOT1, fb = bars + (B_FULL1 + slot) * 8;
          mbar_expect(fb, SLOT1);
          tma_load(base, &maps.x, fb, k * 64, rb * 128);
          for (int a = 0; a < 4; a++) {
            if (a < nw1) tma_load(base + 16384 + a * 8192, &maps.w1, fb, (w1_at0 + a) * 64, k * 64);
            else tma_load(base + 16384 + a * 8192, &maps.wqkv, fb, (q1_at0 + a - nw1) * 64, k * 64);
          }
        }
        const int nh = rank == 0 ? 14 : 13, h0 = rank == 0 ? 0 : 14, o0 = rank == 0 ? 0 : 5;
        const int c0 = (nt & 1) ? 160 * nt + 32 : 160 * nt;
        const int c2 = (nt & 1) ? 160 * nt - 32 : 160 * nt + 128;
        for (int i = 0; i < 10 + nh + 5; i++) {
          const int slot = (i + 3) & 3;
          if (i < 4) {
            if (i == 0) { mbar_wait(bars + (B_EMPTY1 + 2) * 8, 1); mbar_wait(bars + (B_EMPTY1 + 3) * 8, 1); }
            else if (i == 1) mbar_wait(bars + (B_EMPTY1 + 0) * 8, 0);
            else if (i == 2) mbar_wait(bars + (B_EMPTY1 + 1) * 8, 0);
          } else mbar_wait(bars + (B_EMPTY2 + slot) * 8, ((i >> 2) & 1) ^ 1);
          uint32_t base = ring + slot * SLOT2, fb = bars + (B_FULL2 + slot) * 8;
          if (i < 10) {
            mbar_expect(fb, SLOT2);
            tma_load(base, &maps.x, fb, i * 64, rb * 128);
            for (int a = 0; a < 3; a++) tma_load(base + 16384 + a * 8192, &maps.wqkv, fb, (q2_at0 + a) * 64, i * 64);
          } else {
            const int p = i - 10;
            if (p == 0) { TS(16); flag_wait(&g_flags[(F_H + rb2) * FSTR], 7); TS(17); fence_async(); }
            if (p == nh) { TS(18); flag_wait(&g_flags[(F_O + rb2) * FSTR], 8); TS(19); fence_async(); }
            mbar_expect(fb, SLOT2);
            const bool hp = p < nh;
            const int kc = (hp ? h0 + p : o0 + p - nh) * 64;
            const CUtensorMap* ma = hp ? &maps.h : &maps.o;
            const CUtensorMap* mb = hp ? &maps.w2 : &maps.wo;
            tma_load(base, ma, fb, kc, rb2 * 128);
            tma_load(base + 16384, mb, fb, c0, kc);
            tma_load(base + 16384 + 8192, mb, fb, c0 + 64, kc);
            tma_load(base + 16384 + 16384, mb, fb, c2, kc);
          }
        }
        finish_reader();
      }
    }
    __syncwarp();
    asm volatile("barrier.cluster.wait.acquire.aligned;" ::: "memory");
   } else if (!regular) {
    asm volatile("barrier.cluster.wait.acquire.aligned;" ::: "memory");
    if (tid == 32) {
      for (int t = 0; t < 4; t++) {
        mbar_wait(bars + B_STGFULL * 8, t & 1);
        tma_store(&maps.qkv_st, stg, 29 * 64, (xrb + t) * 128);
        bulk_commit_wait();
        mbar_arrive(bars + B_STGFREE * 8);
        flag_add(&g_flags[(F_QKV + xrb + t) * FSTR]);
      }
    }
   } else {
    const int t = tid - 32;
    float* const sGp = reinterpret_cast<float*>(sp + SG_OFF);
    {
      const int ch = t & 7, r0 = t >> 3;
      float dot[11];
#pragma unroll
      for (int i = 0; i < 11; i++) dot[i] = 0.f;
      for (int k = 0; k < 10; k++) {
        uint4 w = __ldg(reinterpret_cast<const uint4*>(gate_w + k * 64 + ch * 8));
        mbar_wait(bars + (B_FULL1 + (k & 3)) * 8, (k >> 2) & 1);
        const uint8_t* abase = sp + (k & 3) * SLOT1;
        uint4 a[11];
#pragma unroll
        for (int i = 0; i < 11; i++) {
          int row = min(r0 + 12 * i, 127);
          a[i] = *reinterpret_cast<const uint4*>(abase + row * 128 + ((ch ^ (row & 7)) << 4));
        }
#pragma unroll
        for (int i = 0; i < 11; i++)
          dot[i] += bf_lo(a[i].x) * bf_lo(w.x) + bf_hi(a[i].x) * bf_hi(w.x) + bf_lo(a[i].y) * bf_lo(w.y) + bf_hi(a[i].y) * bf_hi(w.y)
                  + bf_lo(a[i].z) * bf_lo(w.z) + bf_hi(a[i].z) * bf_hi(w.z) + bf_lo(a[i].w) * bf_lo(w.w) + bf_hi(a[i].w) * bf_hi(w.w);
#pragma unroll
        for (int i = 0; i < 11; i++) asm volatile("" : "+f"(dot[i])::"memory");
        __syncwarp();
        if (lane == 0) mbar_arrive(bars + (B_EMPTY1 + (k & 3)) * 8);
      }
#pragma unroll
      for (int i = 0; i < 11; i++) {
        float d = dot[i];
        d += __shfl_xor_sync(0xffffffffu, d, 1); d += __shfl_xor_sync(0xffffffffu, d, 2); d += __shfl_xor_sync(0xffffffffu, d, 4);
        int row = r0 + 12 * i;
        if (ch == 0 && row < 128) sGp[row] = rcpf(1.f + ex2f(-1.4426950408889634f * d));
      }
      __syncwarp();
      if (lane == 0) mbar_arrive(bars + B_GREADY * 8);
      if (t == 0) TS(8);
    }
    asm volatile("barrier.cluster.wait.acquire.aligned;" ::: "memory");
    if (t == 32) {
      for (int a = 0; a < nw1; a++) {
        mbar_wait(bars + (a == 0 ? B_HDONE : B_HD1 + a - 1) * 8, 0);
        tma_store(&maps.h, stg + a * 16384, (w1_at0 + a) * 64, rb * 128);
      }
      if (nw1 > 0) { bulk_commit_wait(); flag_add(&g_flags[(F_H + rb) * FSTR]); }
      mbar_arrive(bars + B_STGFREE * 8);
      TS(10);
      mbar_wait(bars + B_ODONE * 8, 0);
      TS(28);
      tma_store3(&maps.o_st, stg, 80 * j, rb * 64);
      bulk_commit_wait();
      flag_add(&g_flags[(F_O + rb) * FSTR]);
      mbar_arrive_cl(mapa(bars + B_PEERFREE * 8, rank ^ 1));
      TS(15);
    } else if (t == 0) {
      mbar_wait(bars + B_STGFULL * 8, 0);
      if (nw1 < 4) {
        for (int a = nw1; a < 4; a++) tma_store(&maps.qkv_st, stg + a * 16384, (q1_at0 + a - nw1) * 64, rb * 128);
        bulk_commit_wait();
        flag_add(&g_flags[(F_QKV + rb) * FSTR]);
      }
      mbar_arrive(bars + B_STGFREE * 8);
      mbar_wait(bars + B_STGFULL * 8, 1);
      TS(11);
      for (int a = 0; a < 3; a++) tma_store(&maps.qkv_st, stg + a * 16384, (q2_at0 + a) * 64, rb * 128);
      bulk_commit_wait();
      flag_add(&g_flags[(F_QKV + rb) * FSTR]);
      TS(12);
      flag_wait(&g_flags[(F_QKV + rb) * FSTR], 11);
      if (rb > 0) flag_wait(&g_flags[(F_QKV + rb - 1) * FSTR], 11);
      fence_async();
      TS(13);
      uint32_t fb = bars + B_ATTFULL * 8;
      mbar_expect(fb, 128 * 160 + 2 * 142 * 160);
      tma_load3(stg, &maps.qkv_ldq, fb, 80 * j, rb * 64);
      tma_load3(stg + ATT_K_OFF, &maps.qkv_ldkv, fb, 640 + 80 * j, rb * 64 - 7);
      tma_load3(stg + ATT_V_OFF, &maps.qkv_ldkv, fb, 1280 + 80 * j, rb * 64 - 7);
      finish_reader();
    }
   }
  } else {
    asm volatile("setmaxnreg.inc.sync.aligned.u32 200;");
    const int wg = wgi - 1;
    int slot = 0, cnt = 0;
    if (tid == 128) TS(0);
    const int ct = tid - 128;
    uint8_t* const stp = sp + STG_OFF;
    const float* const sGp = reinterpret_cast<const float*>(sp + SG_OFF);
    auto nobg = [](int) {};
    if (!regular) {
      asm volatile("barrier.cluster.wait.acquire.aligned;" ::: "memory");
      for (int tl = 0; tl < 4; tl++) {
        float acc[32];
        tile_loop<64, 6, SLOTX>(acc, ring, bars + B_FULL1 * 8, bars + B_EMPTY1 * 8, slot, cnt, wg, lane, nobg);
        if (tl > 0) mbar_wait(bars + B_STGFREE * 8, (tl - 1) & 1);
        dump_tile<64>(acc, ring + STG_OFF, wg, warp, lane);
        fence_async_smem();
        named_bar(2, 256);
        if (tid == 128) mbar_arrive(bars + B_STGFULL * 8);
      }
    } else {
      uint4 bv[4];
#pragma unroll
      for (int a = 0; a < 4; a++) bv[a] = __ldg(reinterpret_cast<const uint4*>(b1 + min(w1_at0 + a, 26) * 64 + (ct & 7) * 8));
      {
        float acc[128];
        tile_loop<256, 4, SLOT1>(acc, ring, bars + B_FULL1 * 8, bars + B_EMPTY1 * 8, slot, cnt, wg, lane, nobg);
        if (tid == 128) TS(1);
        named_bar(2, 256);
        dump_tile<256>(acc, ring + STG_OFF, wg, warp, lane);
        fence_async_smem();
        named_bar(2, 256);
      }
      if (tid == 128) { mbar_arrive(bars + B_STGFULL * 8); TS(2); }
      asm volatile("barrier.cluster.wait.acquire.aligned;" ::: "memory");
      slot = 3; cnt = 0;
      {
        float acc[96];
        float omr[4];
        uint4 vn[2];
        tile_loop<192, 4, SLOT2>(acc, ring, bars + B_FULL2 * 8, bars + B_EMPTY2 * 8, slot, cnt, wg, lane, [&](int k1) {
          const int k = k1 - 1;
          if (k == 0) {
            mbar_wait(bars + B_GREADY * 8, 0);
#pragma unroll
            for (int i = 0; i < 4; i++) omr[i] = 1.f - sGp[(ct >> 3) + 32 * i];
            vn[0] = *mish_ptr(stp, 0, 0, ct); vn[1] = *mish_ptr(stp, 0, 1, ct);
          }
          if (k >= 0 && k < nw1) {
            const uint4 b = k == 0 ? bv[0] : k == 1 ? bv[1] : k == 2 ? bv[2] : bv[3];
#pragma unroll 1
            for (int sl = 2 * k; sl < 2 * k + 2; sl++) {
              const uint4 v[2] = {vn[0], vn[1]};
              if (sl + 1 < 2 * nw1) { vn[0] = *mish_ptr(stp, sl + 1, 0, ct); vn[1] = *mish_ptr(stp, sl + 1, 1, ct); }
              mish_slice(stp, omr, b, v, sl, ct);
            }
            warp_done(bars + (k == 0 ? B_HDONE : B_HD1 + k - 1) * 8, lane);
          }
        });
        if (tid == 128) TS(3);
        mbar_wait(bars + B_STGFREE * 8, 0);
        named_bar(2, 256);
        dump_tile<192>(acc, ring + STG_OFF, wg, warp, lane);
        fence_async_smem();
        named_bar(2, 256);
      }
      if (tid == 128) { mbar_arrive(bars + B_STGFULL * 8); TS(4); }

      const int g8 = lane >> 2, c4 = lane & 3;
      const int par = warp & 1, P0 = ((wg * 4 + warp) >> 1) * 16;
      const uint32_t stq = ring + STG_OFF + par * (64 * 160);
      const uint32_t stk = ring + STG_OFF + ATT_K_OFF + par * (71 * 160);
      const uint32_t stv = ring + STG_OFF + ATT_V_OFF + par * (71 * 160);
      int ast = 0;
      auto att_step = [&]() {
        if (tid == 128 && ast == 0) TS(22);
        const bool oddh = (ast & 1) != 0;
        const int hoffb = ast * 40 - (oddh ? 8 : 0);
        uint32_t qa[4], qb[2];
        {
          const uint32_t qrow = stq + (P0 + (lane & 7) + ((lane >> 3) & 1) * 8) * 160 + hoffb;
          ldsm4(qa, qrow + (lane >> 4) * 16);
          ldsm2(qb, qrow + 32);
          if (oddh) { if (c4 < 2) { qa[0] = 0u; qa[1] = 0u; } }
          else if (c4 >= 2) { qb[0] = 0u; qb[1] = 0u; }
        }
        const int chunk = min(lane >> 3, 2);
        float sfr[3][4];
#pragma unroll
        for (int n = 0; n < 3; n++) {
          uint32_t kb[4];
          ldsm4(kb, stk + min(P0 + 8 * n + (lane & 7), 70) * 160 + hoffb + chunk * 16);
          sfr[n][0] = sfr[n][1] = sfr[n][2] = sfr[n][3] = 0.f;
          mma16816(sfr[n], qa[0], qa[1], qa[2], qa[3], kb[0], kb[1]);
          mma16816(sfr[n], qb[0], qb[1], 0u, 0u, kb[2], 0u);
        }
        uint32_t vb[3][4];
#pragma unroll
        for (int d = 0; d < 3; d++) ldsm4t(vb[d], stv + min(P0 + 8 * chunk + (lane & 7), 70) * 160 + hoffb + d * 16);
        const float sc = 0.22360679774997896f * 1.4426950408889634f;
        const int tmin = 7 - (rb * 64 + P0);
        float mx0 = -3.0e38f, mx1 = -3.0e38f;
#pragma unroll
        for (int n = 0; n < 3; n++) {
#pragma unroll
          for (int e = 0; e < 2; e++) {
            const int t = 8 * n + 2 * c4 + e;
            sfr[n][e] = (t >= g8 && t <= g8 + 7 && t >= tmin) ? sfr[n][e] * sc : -3.0e38f;
            sfr[n][2 + e] = (t >= g8 + 8 && t <= g8 + 15 && t >= tmin) ? sfr[n][2 + e] * sc : -3.0e38f;
            mx0 = fmaxf(mx0, sfr[n][e]); mx1 = fmaxf(mx1, sfr[n][2 + e]);
          }
        }
        mx0 = fmaxf(mx0, __shfl_xor_sync(0xffffffffu, mx0, 1)); mx1 = fmaxf(mx1, __shfl_xor_sync(0xffffffffu, mx1, 1));
        mx0 = fmaxf(mx0, __shfl_xor_sync(0xffffffffu, mx0, 2)); mx1 = fmaxf(mx1, __shfl_xor_sync(0xffffffffu, mx1, 2));
        float s0 = 0.f, s1 = 0.f;
#pragma unroll
        for (int n = 0; n < 3; n++) {
#pragma unroll
          for (int e = 0; e < 2; e++) {
            sfr[n][e] = ex2f(sfr[n][e] - mx0); sfr[n][2 + e] = ex2f(sfr[n][2 + e] - mx1);
            s0 += sfr[n][e]; s1 += sfr[n][2 + e];
          }
        }
        s0 += __shfl_xor_sync(0xffffffffu, s0, 1); s1 += __shfl_xor_sync(0xffffffffu, s1, 1);
        s0 += __shfl_xor_sync(0xffffffffu, s0, 2); s1 += __shfl_xor_sync(0xffffffffu, s1, 2);
        const uint32_t p0 = pack_bf16(sfr[0][0], sfr[0][1]), p1 = pack_bf16(sfr[0][2], sfr[0][3]);
        const uint32_t p2 = pack_bf16(sfr[1][0], sfr[1][1]), p3 = pack_bf16(sfr[1][2], sfr[1][3]);
        const uint32_t p4 = pack_bf16(sfr[2][0], sfr[2][1]), p5 = pack_bf16(sfr[2][2], sfr[2][3]);
        const float f0 = sGp[2 * (P0 + g8) + par] * rcpf(s0), f1 = sGp[2 * (P0 + g8 + 8) + par] * rcpf(s1);
        float ofr[3][4];
#pragma unroll
        for (int d = 0; d < 3; d++) {
          ofr[d][0] = ofr[d][1] = ofr[d][2] = ofr[d][3] = 0.f;
          mma16816(ofr[d], p0, p1, p2, p3, vb[d][0], vb[d][1]);
          mma16816(ofr[d], p4, p5, 0u, 0u, vb[d][2], 0u);
        }
        __syncwarp();
        uint8_t* op = stp + par * (64 * 160) + (P0 + g8) * 160 + hoffb + c4 * 4;
#pragma unroll
        for (int d = 0; d < 3; d++) {
          const bool ok = oddh ? (d > 0 || c4 >= 2) : (d < 2 || c4 < 2);
          if (ok) {
            *reinterpret_cast<uint32_t*>(op + d * 16) = pack_bf16(ofr[d][0] * f0, ofr[d][1] * f0);
            *reinterpret_cast<uint32_t*>(op + 8 * 160 + d * 16) = pack_bf16(ofr[d][2] * f1, ofr[d][3] * f1);
          }
        }
        if (ast == 3) {
          warp_done(bars + B_ODONE * 8, lane);
          if (tid == 128) TS(26);
        }
        ast++;
      };
      const int nh = rank == 0 ? 14 : 13;
      float accA[64], accB[16];
      zero_acc(accA); zero_acc(accB);
      const uint64_t hoff = 1024 + ((nt & 1) ? 4 : 0);
      mainloop<4, SLOT2>(ring, bars + B_FULL2 * 8, bars + B_EMPTY2 * 8, slot, cnt, nh + 5, wg, lane, [&](uint64_t da, uint64_t db) {
#pragma unroll
        for (int kk = 0; kk < 4; kk++) {
          wgmma_n128(accA, da + kk * 2, db + kk * 128, 1);
          wgmma_n32(accB, da + kk * 2, db + hoff + kk * 128, 1);
        }
      }, [&](int k) {
        if (k == K_ATT) {
          mbar_wait(bars + B_ATTFULL * 8, 0);
          wg_wait<0>();
#pragma unroll 2
          for (int hh = 0; hh < 4; hh++) att_step();
        }
      });
      pin_acc(accA); pin_acc(accB);
      float acc[80];
#pragma unroll
      for (int i = 0; i < 64; i++) acc[i] = accA[i];
#pragma unroll
      for (int i = 0; i < 16; i++) acc[64 + i] = accB[i];
      const uint32_t peer = rank ^ 1;
      if (tid == 128) TS(5);
      mbar_wait_cl(bars + B_PEERFREE * 8, 0);
      const uint32_t rdst = mapa(ring + STG_OFF + ATT_K_OFF + ct * 16, peer);
      const uint32_t rbar = mapa(bars + B_PEERDATA * 8, peer);
      const bool odd = (nt & 1) != 0;
      float keep[40], snd[40];
#pragma unroll
      for (int i = 0; i < 10; i++) {
        const int be0 = i, be1 = 10 + i;
        const int bo0 = i < 4 ? 16 + i : i - 4, bo1 = 6 + i;
#pragma unroll
        for (int e = 0; e < 4; e++) {
          const float r0 = odd ? acc[4 * bo0 + e] : acc[4 * be0 + e];
          const float r1 = odd ? acc[4 * bo1 + e] : acc[4 * be1 + e];
          keep[4 * i + e] = rank == 0 ? r0 : r1;
          snd[4 * i + e] = rank == 0 ? r1 : r0;
        }
      }
#pragma unroll
      for (int i = 0; i < 10; i++)
        asm volatile("st.async.shared::cluster.mbarrier::complete_tx::bytes.v4.f32 [%0], {%1,%2,%3,%4}, [%5];"
                     ::"r"(rdst + i * 4096), "f"(snd[4 * i]), "f"(snd[4 * i + 1]), "f"(snd[4 * i + 2]), "f"(snd[4 * i + 3]), "r"(rbar) : "memory");
      mbar_wait_cl(bars + B_PEERDATA * 8, 0);
      if (tid == 128) TS(6);
      uint8_t* orow = sp + (wg * 64 + warp * 16 + (lane >> 2)) * 160 + (lane & 3) * 4;
#pragma unroll
      for (int i = 0; i < 10; i++) {
        const float4 v = *reinterpret_cast<const float4*>(stp + ATT_K_OFF + ct * 16 + i * 4096);
        *reinterpret_cast<uint32_t*>(orow + i * 16) = pack_bf16(v.x + keep[4 * i], v.y + keep[4 * i + 1]);
        *reinterpret_cast<uint32_t*>(orow + 8 * 160 + i * 16) = pack_bf16(v.z + keep[4 * i + 2], v.w + keep[4 * i + 3]);
      }
      fence_async_smem();
      named_bar(2, 256);
      if (tid == 128) {
        tma_store(&maps.out_st, ring, 160 * nt + 80 * rank, rb2 * 128);
        asm volatile("cp.async.bulk.commit_group;" ::: "memory");
        asm volatile("cp.async.bulk.wait_group.read 0;" ::: "memory");
      }
      if (tid == 128) TS(7);
    }
  }
}

typedef CUresult (*EncFn)(CUtensorMap*, CUtensorMapDataType, cuuint32_t, void*, const cuuint64_t*, const cuuint64_t*,
                          const cuuint32_t*, const cuuint32_t*, CUtensorMapInterleave, CUtensorMapSwizzle,
                          CUtensorMapL2promotion, CUtensorMapFloatOOBfill);

void make_map(EncFn enc, CUtensorMap* m, const void* p, int cols, int rows, int bc, int br, bool swz) {
  cuuint64_t d[2] = {(cuuint64_t)cols, (cuuint64_t)rows};
  cuuint64_t s[1] = {(cuuint64_t)cols * 2};
  cuuint32_t b[2] = {(cuuint32_t)bc, (cuuint32_t)br};
  cuuint32_t e[2] = {1, 1};
  enc(m, CU_TENSOR_MAP_DATA_TYPE_BFLOAT16, 2, const_cast<void*>(p), d, s, b, e, CU_TENSOR_MAP_INTERLEAVE_NONE,
      swz ? CU_TENSOR_MAP_SWIZZLE_128B : CU_TENSOR_MAP_SWIZZLE_NONE, CU_TENSOR_MAP_L2_PROMOTION_L2_128B,
      CU_TENSOR_MAP_FLOAT_OOB_FILL_NONE);
}

void make_map3(EncFn enc, CUtensorMap* m, const void* p, int cols, int rows, int bc, int bpairs) {
  cuuint64_t d[3] = {(cuuint64_t)cols, (cuuint64_t)rows / 2, 2};
  cuuint64_t s[2] = {(cuuint64_t)cols * 4, (cuuint64_t)cols * 2};
  cuuint32_t b[3] = {(cuuint32_t)bc, (cuuint32_t)bpairs, 2};
  cuuint32_t e[3] = {1, 1, 1};
  enc(m, CU_TENSOR_MAP_DATA_TYPE_BFLOAT16, 3, const_cast<void*>(p), d, s, b, e, CU_TENSOR_MAP_INTERLEAVE_NONE,
      CU_TENSOR_MAP_SWIZZLE_NONE, CU_TENSOR_MAP_L2_PROMOTION_L2_128B, CU_TENSOR_MAP_FLOAT_OOB_FILL_NONE);
}

}

extern "C" void kernel_launch(void* const* d_in, const int* in_sizes, int n_in, void* d_out, int out_size) {
  (void)in_sizes; (void)n_in; (void)out_size;
  static Maps maps;
  static const void* seen[9] = {nullptr};
  bool same = seen[8] == d_out;
  for (int i = 0; i < 8; i++) same = same && seen[i] == d_in[i];
  if (!same) {
    for (int i = 0; i < 8; i++) seen[i] = d_in[i];
    seen[8] = d_out;
    EncFn enc = nullptr;
    cudaDriverEntryPointQueryResult q;
    cudaGetDriverEntryPoint("cuTensorMapEncodeTiled", (void**)&enc, cudaEnableDefault, &q);
    void *ph, *po, *pq;
    cudaGetSymbolAddress(&ph, g_h);
    cudaGetSymbolAddress(&po, g_o);
    cudaGetSymbolAddress(&pq, g_qkv);
    make_map(enc, &maps.x, d_in[0], DM, SEQ, 64, 128, true);
    make_map(enc, &maps.wqkv, d_in[1], QKVN, DM, 64, 64, true);
    make_map(enc, &maps.wo, d_in[2], DM, DM, 64, 64, true);
    make_map(enc, &maps.w1, d_in[4], FF, DM, 64, 64, true);
    make_map(enc, &maps.w2, d_in[6], DM, FF, 64, 64, true);
    make_map(enc, &maps.h, ph, FF, SEQ, 64, 128, true);
    make_map(enc, &maps.o, po, DM, SEQ, 64, 128, true);
    make_map(enc, &maps.qkv_st, pq, QKVN, SEQ, 64, 128, true);
    make_map3(enc, &maps.qkv_ldq, pq, QKVN, SEQ, 80, 64);
    make_map3(enc, &maps.qkv_ldkv, pq, QKVN, SEQ, 80, 71);
    make_map3(enc, &maps.o_st, po, DM, SEQ, 80, 64);
    make_map(enc, &maps.out_st, d_out, DM, SEQ, 80, 128, false);
    cudaFuncSetAttribute(fused_kernel, cudaFuncAttributeMaxDynamicSharedMemorySize, SMEM_ALLOC);
  }
  fused_kernel<<<NCTAS, NTHREADS, SMEM_ALLOC>>>(maps, (const __nv_bfloat16*)d_in[5], (const __nv_bfloat16*)d_in[7],
                                               (const uint8_t*)d_in[1], (const uint8_t*)d_in[6], (const uint8_t*)d_in[2]);
}
```

```cpp
#include <cuda_runtime.h>
#include <cuda.h>
#include <cuda_bf16.h>
#include <stdint.h>

namespace {

constexpr int SEQ = 2048, DM = 640, FF = 1728, QKVN = 1920;
constexpr int NTHREADS = 384;
constexpr int NREG_CTAS = 128;
constexpr int NCTAS = 132;

#define K_ATT 7

constexpr int RING_BYTES = 163840;
constexpr int SLOT1 = 49152;
constexpr int SLOT2 = 40960;
constexpr int SLOTX = 24576;
constexpr int STG_OFF = RING_BYTES;
constexpr int STG_BYTES = 66048;
constexpr int ATT_K_OFF = 20480;
constexpr int ATT_V_OFF = 43264;
constexpr int MISC_OFF = STG_OFF + STG_BYTES;
constexpr int SG_OFF = MISC_OFF + 256;
constexpr int SMEM_USED = SG_OFF + 1024;
constexpr int SMEM_ALLOC = SMEM_USED + 1024;

enum { B_FULL1 = 0, B_EMPTY1 = 6, B_FULL2 = 12, B_EMPTY2 = 16,
       B_STGFULL = 20, B_GREADY = 21, B_ATTFULL = 22, B_PEERFREE = 23, B_PEERDATA = 24, B_HDONE = 25, B_ODONE = 26,
       B_STGFREE = 27, B_HD1 = 28, B_COUNT = 31 };

enum { F_H = 0, F_QKV = 16, F_O = 32, F_FIN = 48 };
constexpr int FSTR = 32;

__device__ __nv_bfloat16 g_h[SEQ * FF];
__device__ __nv_bfloat16 g_o[SEQ * DM];
__device__ __nv_bfloat16 g_qkv[SEQ * QKVN];
__device__ unsigned g_flags[64 * 32];

struct Maps { CUtensorMap x, wqkv, w1, w2, wo, h, o, qkv_st, qkv_ldq, qkv_ldkv, o_st, out_st; };

__device__ __forceinline__ uint32_t s2u(const void* p) { return (uint32_t)__cvta_generic_to_shared(p); }
__device__ __forceinline__ void mbar_init(uint32_t b, int c) { asm volatile("mbarrier.init.shared::cta.b64 [%0], %1;" ::"r"(b), "r"(c)); }
__device__ __forceinline__ void mbar_expect(uint32_t b, int bytes) { asm volatile("mbarrier.arrive.expect_tx.shared::cta.b64 _, [%0], %1;" ::"r"(b), "r"(bytes) : "memory"); }
__device__ __forceinline__ void mbar_arrive(uint32_t b) { asm volatile("mbarrier.arrive.shared::cta.b64 _, [%0];" ::"r"(b) : "memory"); }
__device__ __forceinline__ bool mbar_try(uint32_t b, int par) {
  uint32_t ok;
  asm volatile("{\n.reg .pred p;\nmbarrier.try_wait.parity.shared::cta.b64 p, [%1], %2;\nselp.u32 %0, 1, 0, p;\n}" : "=r"(ok) : "r"(b), "r"(par) : "memory");
  return ok != 0;
}
__device__ __forceinline__ bool mbar_test(uint32_t b, int par) {
  uint32_t ok;
  asm volatile("{\n.reg .pred p;\nmbarrier.test_wait.parity.shared::cta.b64 p, [%1], %2;\nselp.u32 %0, 1, 0, p;\n}" : "=r"(ok) : "r"(b), "r"(par) : "memory");
  return ok != 0;
}
#define TRAP(c, e) __trap()
__device__ __forceinline__ void mbar_wait(uint32_t b, int par) {
  uint32_t n = 0;
  while (!mbar_try(b, par)) { if (++n > (1u << 22)) TRAP(1, (b & 255) / 8 + 1000 * par); }
}
__device__ __forceinline__ bool mbar_try_cl(uint32_t b, int par) {
  uint32_t ok;
  asm volatile("{\n.reg .pred p;\nmbarrier.try_wait.parity.acquire.cluster.shared::cta.b64 p, [%1], %2;\nselp.u32 %0, 1, 0, p;\n}" : "=r"(ok) : "r"(b), "r"(par) : "memory");
  return ok != 0;
}
__device__ __forceinline__ void mbar_wait_cl(uint32_t b, int par) {
  uint32_t n = 0;
  while (!mbar_try_cl(b, par)) { if (++n > (1u << 22)) TRAP(2, (b & 255) / 8); }
}
__device__ __forceinline__ uint32_t mapa(uint32_t a, uint32_t cta) { uint32_t r; asm volatile("mapa.shared::cluster.u32 %0, %1, %2;" : "=r"(r) : "r"(a), "r"(cta)); return r; }
__device__ __forceinline__ void mbar_arrive_cl(uint32_t remote) { asm volatile("mbarrier.arrive.release.cluster.shared::cluster.b64 _, [%0];" ::"r"(remote) : "memory"); }
__device__ __forceinline__ void tma_load(uint32_t dst, const CUtensorMap* m, uint32_t bar, int c0, int c1) {
  asm volatile("cp.async.bulk.tensor.2d.shared::cluster.global.mbarrier::complete_tx::bytes [%0], [%1, {%3,%4}], [%2];" ::"r"(dst), "l"(m), "r"(bar), "r"(c0), "r"(c1) : "memory");
}
__device__ __forceinline__ void tma_load3(uint32_t dst, const CUtensorMap* m, uint32_t bar, int c0, int c1) {
  asm volatile("cp.async.bulk.tensor.3d.shared::cluster.global.mbarrier::complete_tx::bytes [%0], [%1, {%3,%4,%5}], [%2];" ::"r"(dst), "l"(m), "r"(bar), "r"(c0), "r"(c1), "r"(0) : "memory");
}
__device__ __forceinline__ void tma_store3(const CUtensorMap* m, uint32_t src, int c0, int c1) {
  asm volatile("cp.async.bulk.tensor.3d.global.shared::cta.bulk_group [%0, {%2,%3,%4}], [%1];" ::"l"(m), "r"(src), "r"(c0), "r"(c1), "r"(0) : "memory");
}
__device__ __forceinline__ void tma_store(const CUtensorMap* m, uint32_t src, int c0, int c1) {
  asm volatile("cp.async.bulk.tensor.2d.global.shared::cta.bulk_group [%0, {%2,%3}], [%1];" ::"l"(m), "r"(src), "r"(c0), "r"(c1) : "memory");
}
__device__ __forceinline__ void fence_async() { asm volatile("fence.proxy.async.global;" ::: "memory"); }
__device__ __forceinline__ void fence_async_smem() { asm volatile("fence.proxy.async.shared::cta;" ::: "memory"); }
__device__ __forceinline__ void wg_fence() { asm volatile("wgmma.fence.sync.aligned;" ::: "memory"); }
__device__ __forceinline__ void wg_commit() { asm volatile("wgmma.commit_group.sync.aligned;" ::: "memory"); }
template <int N> __device__ __forceinline__ void wg_wait() { asm volatile("wgmma.wait_group.sync.aligned %0;" ::"n"(N) : "memory"); }
__device__ __forceinline__ void named_bar(int id, int n) { asm volatile("bar.sync %0, %1;" ::"r"(id), "r"(n) : "memory"); }
__device__ __forceinline__ unsigned ld_rlx(const unsigned* p) { unsigned v; asm volatile("ld.relaxed.gpu.global.u32 %0, [%1];" : "=r"(v) : "l"(p) : "memory"); return v; }
__device__ __forceinline__ void flag_add(unsigned* p) { asm volatile("red.relaxed.gpu.global.add.u32 [%0], 1;" ::"l"(p) : "memory"); }
__device__ __forceinline__ void flag_wait(const unsigned* p, unsigned target) {
  uint32_t n = 0;
  while (ld_rlx(p) < target) { __nanosleep(32); if (++n > (1u << 20)) TRAP(3, (unsigned)(p - g_flags)); }
}
__device__ __forceinline__ void bulk_commit_wait() {
  asm volatile("cp.async.bulk.commit_group;" ::: "memory");
  asm volatile("cp.async.bulk.wait_group 0;" ::: "memory");
}
__device__ __forceinline__ void finish_reader() {
  unsigned old = atomicAdd(&g_flags[F_FIN * FSTR], 1u);
  if (old == 2 * NREG_CTAS - 1) {
    for (int i = 0; i <= F_FIN; i++) g_flags[i * FSTR] = 0;
  }
}
#define TS(i)
#define TR()
__device__ __forceinline__ uint32_t pack_bf16(float a, float b) { __nv_bfloat162 t = __floats2bfloat162_rn(a, b); return *reinterpret_cast<uint32_t*>(&t); }
__device__ __forceinline__ float bf_lo(uint32_t v) { return __uint_as_float(v << 16); }
__device__ __forceinline__ float bf_hi(uint32_t v) { return __uint_as_float(v & 0xffff0000u); }

__device__ __forceinline__ uint64_t desc_a(uint32_t a) { return (uint64_t)((a & 0x3FFFF) >> 4) | (1ull << 16) | (64ull << 32) | (1ull << 62); }
__device__ __forceinline__ uint64_t desc_b(uint32_t a) { return (uint64_t)((a & 0x3FFFF) >> 4) | (512ull << 16) | (64ull << 32) | (1ull << 62); }

__device__ __forceinline__ void wgmma_n256(float (&d)[128], uint64_t da, uint64_t db, int sc) {
  asm volatile("{\n.reg .pred p;\nsetp.ne.b32 p, %130, 0;\n"
    "wgmma.mma_async.sync.aligned.m64n256k16.f32.bf16.bf16 {%0, %1, %2, %3, %4, %5, %6, %7, %8, %9, %10, %11, %12, %13, %14, %15, %16, %17, %18, %19, %20, %21, %22, %23, %24, %25, %26, %27, %28, %29, %30, %31, %32, %33, %34, %35, %36, %37, %38, %39, %40, %41, %42, %43, %44, %45, %46, %47, %48, %49, %50, %51, %52, %53, %54, %55, %56, %57, %58, %59, %60, %61, %62, %63, %64, %65, %66, %67, %68, %69, %70, %71, %72, %73, %74, %75, %76, %77, %78, %79, %80, %81, %82, %83, %84, %85, %86, %87, %88, %89, %90, %91, %92, %93, %94, %95, %96, %97, %98, %99, %100, %101, %102, %103, %104, %105, %106, %107, %108, %109, %110, %111, %112, %113, %114, %115, %116, %117, %118, %119, %120, %121, %122, %123, %124, %125, %126, %127}, %128, %129, p, 1, 1, 0, 1;\n}\n"
    : "+f"(d[0]), "+f"(d[1]), "+f"(d[2]), "+f"(d[3]), "+f"(d[4]), "+f"(d[5]), "+f"(d[6]), "+f"(d[7]), "+f"(d[8]), "+f"(d[9]), "+f"(d[10]), "+f"(d[11]), "+f"(d[12]), "+f"(d[13]), "+f"(d[14]), "+f"(d[15]), "+f"(d[16]), "+f"(d[17]), "+f"(d[18]), "+f"(d[19]), "+f"(d[20]), "+f"(d[21]), "+f"(d[22]), "+f"(d[23]), "+f"(d[24]), "+f"(d[25]), "+f"(d[26]), "+f"(d[27]), "+f"(d[28]), "+f"(d[29]), "+f"(d[30]), "+f"(d[31]), "+f"(d[32]), "+f"(d[33]), "+f"(d[34]), "+f"(d[35]), "+f"(d[36]), "+f"(d[37]), "+f"(d[38]), "+f"(d[39]), "+f"(d[40]), "+f"(d[41]), "+f"(d[42]), "+f"(d[43]), "+f"(d[44]), "+f"(d[45]), "+f"(d[46]), "+f"(d[47]), "+f"(d[48]), "+f"(d[49]), "+f"(d[50]), "+f"(d[51]), "+f"(d[52]), "+f"(d[53]), "+f"(d[54]), "+f"(d[55]), "+f"(d[56]), "+f"(d[57]), "+f"(d[58]), "+f"(d[59]), "+f"(d[60]), "+f"(d[61]), "+f"(d[62]), "+f"(d[63]), "+f"(d[64]), "+f"(d[65]), "+f"(d[66]), "+f"(d[67]), "+f"(d[68]), "+f"(d[69]), "+f"(d[70]), "+f"(d[71]), "+f"(d[72]), "+f"(d[73]), "+f"(d[74]), "+f"(d[75]), "+f"(d[76]), "+f"(d[77]), "+f"(d[78]), "+f"(d[79]), "+f"(d[80]), "+f"(d[81]), "+f"(d[82]), "+f"(d[83]), "+f"(d[84]), "+f"(d[85]), "+f"(d[86]), "+f"(d[87]), "+f"(d[88]), "+f"(d[89]), "+f"(d[90]), "+f"(d[91]), "+f"(d[92]), "+f"(d[93]), "+f"(d[94]), "+f"(d[95]), "+f"(d[96]), "+f"(d[97]), "+f"(d[98]), "+f"(d[99]), "+f"(d[100]), "+f"(d[101]), "+f"(d[102]), "+f"(d[103]), "+f"(d[104]), "+f"(d[105]), "+f"(d[106]), "+f"(d[107]), "+f"(d[108]), "+f"(d[109]), "+f"(d[110]), "+f"(d[111]), "+f"(d[112]), "+f"(d[113]), "+f"(d[114]), "+f"(d[115]), "+f"(d[116]), "+f"(d[117]), "+f"(d[118]), "+f"(d[119]), "+f"(d[120]), "+f"(d[121]), "+f"(d[122]), "+f"(d[123]), "+f"(d[124]), "+f"(d[125]), "+f"(d[126]), "+f"(d[127])
    : "l"(da), "l"(db), "r"(sc));
}
__device__ __forceinline__ void wgmma_n192(float (&d)[96], uint64_t da, uint64_t db, int sc) {
  asm volatile("{\n.reg .pred p;\nsetp.ne.b32 p, %98, 0;\n"
    "wgmma.mma_async.sync.aligned.m64n192k16.f32.bf16.bf16 {%0, %1, %2, %3, %4, %5, %6, %7, %8, %9, %10, %11, %12, %13, %14, %15, %16, %17, %18, %19, %20, %21, %22, %23, %24, %25, %26, %27, %28, %29, %30, %31, %32, %33, %34, %35, %36, %37, %38, %39, %40, %41, %42, %43, %44, %45, %46, %47, %48, %49, %50, %51, %52, %53, %54, %55, %56, %57, %58, %59, %60, %61, %62, %63, %64, %65, %66, %67, %68, %69, %70, %71, %72, %73, %74, %75, %76, %77, %78, %79, %80, %81, %82, %83, %84, %85, %86, %87, %88, %89, %90, %91, %92, %93, %94, %95}, %96, %97, p, 1, 1, 0, 1;\n}\n"
    : "+f"(d[0]), "+f"(d[1]), "+f"(d[2]), "+f"(d[3]), "+f"(d[4]), "+f"(d[5]), "+f"(d[6]), "+f"(d[7]), "+f"(d[8]), "+f"(d[9]), "+f"(d[10]), "+f"(d[11]), "+f"(d[12]), "+f"(d[13]), "+f"(d[14]), "+f"(d[15]), "+f"(d[16]), "+f"(d[17]), "+f"(d[18]), "+f"(d[19]), "+f"(d[20]), "+f"(d[21]), "+f"(d[22]), "+f"(d[23]), "+f"(d[24]), "+f"(d[25]), "+f"(d[26]), "+f"(d[27]), "+f"(d[28]), "+f"(d[29]), "+f"(d[30]), "+f"(d[31]), "+f"(d[32]), "+f"(d[33]), "+f"(d[34]), "+f"(d[35]), "+f"(d[36]), "+f"(d[37]), "+f"(d[38]), "+f"(d[39]), "+f"(d[40]), "+f"(d[41]), "+f"(d[42]), "+f"(d[43]), "+f"(d[44]), "+f"(d[45]), "+f"(d[46]), "+f"(d[47]), "+f"(d[48]), "+f"(d[49]), "+f"(d[50]), "+f"(d[51]), "+f"(d[52]), "+f"(d[53]), "+f"(d[54]), "+f"(d[55]), "+f"(d[56]), "+f"(d[57]), "+f"(d[58]), "+f"(d[59]), "+f"(d[60]), "+f"(d[61]), "+f"(d[62]), "+f"(d[63]), "+f"(d[64]), "+f"(d[65]), "+f"(d[66]), "+f"(d[67]), "+f"(d[68]), "+f"(d[69]), "+f"(d[70]), "+f"(d[71]), "+f"(d[72]), "+f"(d[73]), "+f"(d[74]), "+f"(d[75]), "+f"(d[76]), "+f"(d[77]), "+f"(d[78]), "+f"(d[79]), "+f"(d[80]), "+f"(d[81]), "+f"(d[82]), "+f"(d[83]), "+f"(d[84]), "+f"(d[85]), "+f"(d[86]), "+f"(d[87]), "+f"(d[88]), "+f"(d[89]), "+f"(d[90]), "+f"(d[91]), "+f"(d[92]), "+f"(d[93]), "+f"(d[94]), "+f"(d[95])
    : "l"(da), "l"(db), "r"(sc));
}
__device__ __forceinline__ void wgmma_n160(float (&d)[80], uint64_t da, uint64_t db, int sc) {
  asm volatile("{\n.reg .pred p;\nsetp.ne.b32 p, %82, 0;\n"
    "wgmma.mma_async.sync.aligned.m64n160k16.f32.bf16.bf16 {%0, %1, %2, %3, %4, %5, %6, %7, %8, %9, %10, %11, %12, %13, %14, %15, %16, %17, %18, %19, %20, %21, %22, %23, %24, %25, %26, %27, %28, %29, %30, %31, %32, %33, %34, %35, %36, %37, %38, %39, %40, %41, %42, %43, %44, %45, %46, %47, %48, %49, %50, %51, %52, %53, %54, %55, %56, %57, %58, %59, %60, %61, %62, %63, %64, %65, %66, %67, %68, %69, %70, %71, %72, %73, %74, %75, %76, %77, %78, %79}, %80, %81, p, 1, 1, 0, 1;\n}\n"
    : "+f"(d[0]), "+f"(d[1]), "+f"(d[2]), "+f"(d[3]), "+f"(d[4]), "+f"(d[5]), "+f"(d[6]), "+f"(d[7]), "+f"(d[8]), "+f"(d[9]), "+f"(d[10]), "+f"(d[11]), "+f"(d[12]), "+f"(d[13]), "+f"(d[14]), "+f"(d[15]), "+f"(d[16]), "+f"(d[17]), "+f"(d[18]), "+f"(d[19]), "+f"(d[20]), "+f"(d[21]), "+f"(d[22]), "+f"(d[23]), "+f"(d[24]), "+f"(d[25]), "+f"(d[26]), "+f"(d[27]), "+f"(d[28]), "+f"(d[29]), "+f"(d[30]), "+f"(d[31]), "+f"(d[32]), "+f"(d[33]), "+f"(d[34]), "+f"(d[35]), "+f"(d[36]), "+f"(d[37]), "+f"(d[38]), "+f"(d[39]), "+f"(d[40]), "+f"(d[41]), "+f"(d[42]), "+f"(d[43]), "+f"(d[44]), "+f"(d[45]), "+f"(d[46]), "+f"(d[47]), "+f"(d[48]), "+f"(d[49]), "+f"(d[50]), "+f"(d[51]), "+f"(d[52]), "+f"(d[53]), "+f"(d[54]), "+f"(d[55]), "+f"(d[56]), "+f"(d[57]), "+f"(d[58]), "+f"(d[59]), "+f"(d[60]), "+f"(d[61]), "+f"(d[62]), "+f"(d[63]), "+f"(d[64]), "+f"(d[65]), "+f"(d[66]), "+f"(d[67]), "+f"(d[68]), "+f"(d[69]), "+f"(d[70]), "+f"(d[71]), "+f"(d[72]), "+f"(d[73]), "+f"(d[74]), "+f"(d[75]), "+f"(d[76]), "+f"(d[77]), "+f"(d[78]), "+f"(d[79])
    : "l"(da), "l"(db), "r"(sc));
}
__device__ __forceinline__ void wgmma_n128(float (&d)[64], uint64_t da, uint64_t db, int sc) {
  asm volatile("{\n.reg .pred p;\nsetp.ne.b32 p, %66, 0;\n"
    "wgmma.mma_async.sync.aligned.m64n128k16.f32.bf16.bf16 {%0, %1, %2, %3, %4, %5, %6, %7, %8, %9, %10, %11, %12, %13, %14, %15, %16, %17, %18, %19, %20, %21, %22, %23, %24, %25, %26, %27, %28, %29, %30, %31, %32, %33, %34, %35, %36, %37, %38, %39, %40, %41, %42, %43, %44, %45, %46, %47, %48, %49, %50, %51, %52, %53, %54, %55, %56, %57, %58, %59, %60, %61, %62, %63}, %64, %65, p, 1, 1, 0, 1;\n}\n"
    : "+f"(d[0]), "+f"(d[1]), "+f"(d[2]), "+f"(d[3]), "+f"(d[4]), "+f"(d[5]), "+f"(d[6]), "+f"(d[7]), "+f"(d[8]), "+f"(d[9]), "+f"(d[10]), "+f"(d[11]), "+f"(d[12]), "+f"(d[13]), "+f"(d[14]), "+f"(d[15]), "+f"(d[16]), "+f"(d[17]), "+f"(d[18]), "+f"(d[19]), "+f"(d[20]), "+f"(d[21]), "+f"(d[22]), "+f"(d[23]), "+f"(d[24]), "+f"(d[25]), "+f"(d[26]), "+f"(d[27]), "+f"(d[28]), "+f"(d[29]), "+f"(d[30]), "+f"(d[31]), "+f"(d[32]), "+f"(d[33]), "+f"(d[34]), "+f"(d[35]), "+f"(d[36]), "+f"(d[37]), "+f"(d[38]), "+f"(d[39]), "+f"(d[40]), "+f"(d[41]), "+f"(d[42]), "+f"(d[43]), "+f"(d[44]), "+f"(d[45]), "+f"(d[46]), "+f"(d[47]), "+f"(d[48]), "+f"(d[49]), "+f"(d[50]), "+f"(d[51]), "+f"(d[52]), "+f"(d[53]), "+f"(d[54]), "+f"(d[55]), "+f"(d[56]), "+f"(d[57]), "+f"(d[58]), "+f"(d[59]), "+f"(d[60]), "+f"(d[61]), "+f"(d[62]), "+f"(d[63])
    : "l"(da), "l"(db), "r"(sc));
}
__device__ __forceinline__ void wgmma_n64(float (&d)[32], uint64_t da, uint64_t db, int sc) {
  asm volatile("{\n.reg .pred p;\nsetp.ne.b32 p, %34, 0;\n"
    "wgmma.mma_async.sync.aligned.m64n64k16.f32.bf16.bf16 {%0, %1, %2, %3, %4, %5, %6, %7, %8, %9, %10, %11, %12, %13, %14, %15, %16, %17, %18, %19, %20, %21, %22, %23, %24, %25, %26, %27, %28, %29, %30, %31}, %32, %33, p, 1, 1, 0, 1;\n}\n"
    : "+f"(d[0]), "+f"(d[1]), "+f"(d[2]), "+f"(d[3]), "+f"(d[4]), "+f"(d[5]), "+f"(d[6]), "+f"(d[7]), "+f"(d[8]), "+f"(d[9]), "+f"(d[10]), "+f"(d[11]), "+f"(d[12]), "+f"(d[13]), "+f"(d[14]), "+f"(d[15]), "+f"(d[16]), "+f"(d[17]), "+f"(d[18]), "+f"(d[19]), "+f"(d[20]), "+f"(d[21]), "+f"(d[22]), "+f"(d[23]), "+f"(d[24]), "+f"(d[25]), "+f"(d[26]), "+f"(d[27]), "+f"(d[28]), "+f"(d[29]), "+f"(d[30]), "+f"(d[31])
    : "l"(da), "l"(db), "r"(sc));
}
__device__ __forceinline__ void wgmma_n32(float (&d)[16], uint64_t da, uint64_t db, int sc) {
  asm volatile("{\n.reg .pred p;\nsetp.ne.b32 p, %18, 0;\n"
    "wgmma.mma_async.sync.aligned.m64n32k16.f32.bf16.bf16 {%0, %1, %2, %3, %4, %5, %6, %7, %8, %9, %10, %11, %12, %13, %14, %15}, %16, %17, p, 1, 1, 0, 1;\n}\n"
    : "+f"(d[0]), "+f"(d[1]), "+f"(d[2]), "+f"(d[3]), "+f"(d[4]), "+f"(d[5]), "+f"(d[6]), "+f"(d[7]), "+f"(d[8]), "+f"(d[9]), "+f"(d[10]), "+f"(d[11]), "+f"(d[12]), "+f"(d[13]), "+f"(d[14]), "+f"(d[15])
    : "l"(da), "l"(db), "r"(sc));
}

template <int N> struct MMA;
template <> struct MMA<256> { static __device__ __forceinline__ void run(float (&d)[128], uint64_t a, uint64_t b, int s) { wgmma_n256(d, a, b, s); } };
template <> struct MMA<192> { static __device__ __forceinline__ void run(float (&d)[96], uint64_t a, uint64_t b, int s) { wgmma_n192(d, a, b, s); } };
template <> struct MMA<160> { static __device__ __forceinline__ void run(float (&d)[80], uint64_t a, uint64_t b, int s) { wgmma_n160(d, a, b, s); } };
template <> struct MMA<64>  { static __device__ __forceinline__ void run(float (&d)[32], uint64_t a, uint64_t b, int s) { wgmma_n64(d, a, b, s); } };

template <int NS, int SLOTB, class ISSUE, class BG>
__device__ __forceinline__ void mainloop(uint32_t ring, uint32_t fullb, uint32_t emptyb, int& slot, int& cnt, int nk,
                                         int wg, int lane, ISSUE&& issue, BG&& bg) {
  int prev = -1;
  for (int k = 0; k < nk; k++) {
    if (!mbar_test(fullb + slot * 8, (cnt / NS) & 1)) {
      if (prev >= 0) {
        wg_wait<0>();
        if (lane == 0) mbar_arrive(emptyb + prev * 8);
        prev = -1;
      }
      mbar_wait(fullb + slot * 8, (cnt / NS) & 1);
    }
    uint32_t base = ring + slot * SLOTB;
    TR();
    wg_fence();
    issue(desc_a(base + wg * 8192), desc_b(base + 16384));
    wg_commit();
    wg_wait<1>();
    if (prev >= 0 && lane == 0) mbar_arrive(emptyb + prev * 8);
    bg(k);
    prev = slot;
    cnt++;
    if (++slot == NS) slot = 0;
  }
  wg_wait<0>();
  if (lane == 0) mbar_arrive(emptyb + prev * 8);
}
template <int R> __device__ __forceinline__ void zero_acc(float (&a)[R]) {
#pragma unroll
  for (int i = 0; i < R; i++) a[i] = 0.f;
}
template <int R> __device__ __forceinline__ void pin_acc(float (&a)[R]) {
#pragma unroll
  for (int i = 0; i < R; i++) asm volatile("" : "+f"(a[i])::"memory");
}
template <int N, int NS, int SLOTB, class BG>
__device__ __forceinline__ void tile_loop(float (&acc)[N / 2], uint32_t ring, uint32_t fullb, uint32_t emptyb,
                                          int& slot, int& cnt, int wg, int lane, BG&& bg) {
  zero_acc(acc);
  mainloop<NS, SLOTB>(ring, fullb, emptyb, slot, cnt, 10, wg, lane, [&](uint64_t da, uint64_t db) {
#pragma unroll
    for (int kk = 0; kk < 4; kk++) MMA<N>::run(acc, da + kk * 2, db + kk * 128, 1);
  }, bg);
  pin_acc(acc);
}

template <int N>
__device__ __forceinline__ void dump_tile(float (&acc)[N / 2], uint32_t stg, int wg, int warp, int lane) {
  int row = wg * 64 + warp * 16 + (lane & 7) + ((lane >> 3) & 1) * 8;
  uint32_t rbase = stg + row * 128;
  int csel = lane >> 4;
#pragma unroll
  for (int jb = 0; jb < N / 8; jb += 2) {
    uint32_t r0 = pack_bf16(acc[4 * jb + 0], acc[4 * jb + 1]);
    uint32_t r1 = pack_bf16(acc[4 * jb + 2], acc[4 * jb + 3]);
    uint32_t r2 = pack_bf16(acc[4 * jb + 4], acc[4 * jb + 5]);
    uint32_t r3 = pack_bf16(acc[4 * jb + 6], acc[4 * jb + 7]);
    int cb = jb + csel;
    uint32_t addr = rbase + (cb >> 3) * 16384 + (((cb & 7) ^ (row & 7)) << 4);
    asm volatile("stmatrix.sync.aligned.m8n8.x4.shared.b16 [%0], {%1,%2,%3,%4};" ::"r"(addr), "r"(r0), "r"(r1), "r"(r2), "r"(r3) : "memory");
  }
}

__device__ __forceinline__ float ex2f(float x) { float y; asm("ex2.approx.ftz.f32 %0, %1;" : "=f"(y) : "f"(x)); return y; }
__device__ __forceinline__ float rcpf(float x) { float y; asm("rcp.approx.ftz.f32 %0, %1;" : "=f"(y) : "f"(x)); return y; }

__device__ __forceinline__ float mish_f(float x, float om, float om2) {
  float e = ex2f(x * 1.4426950408889634f);
  float r = rcpf(fmaf(e, e + 2.f, 2.f));
  return x * fmaf(r, om2, om);
}
__device__ __forceinline__ uint32_t mish2(uint32_t v, uint32_t b, float om, float om2) {
  __nv_bfloat162 x2 = __hadd2(*reinterpret_cast<__nv_bfloat162*>(&v), *reinterpret_cast<__nv_bfloat162*>(&b));
  const uint32_t x = *reinterpret_cast<uint32_t*>(&x2);
  return pack_bf16(mish_f(bf_lo(x), om, om2), mish_f(bf_hi(x), om, om2));
}

__device__ __forceinline__ void mma16816(float (&c)[4], uint32_t a0, uint32_t a1, uint32_t a2, uint32_t a3, uint32_t b0, uint32_t b1) {
  asm volatile("mma.sync.aligned.m16n8k16.row.col.f32.bf16.bf16.f32 {%0,%1,%2,%3}, {%4,%5,%6,%7}, {%8,%9}, {%0,%1,%2,%3};"
               : "+f"(c[0]), "+f"(c[1]), "+f"(c[2]), "+f"(c[3]) : "r"(a0), "r"(a1), "r"(a2), "r"(a3), "r"(b0), "r"(b1));
}

__device__ __forceinline__ void ldsm4(uint32_t (&r)[4], uint32_t a) {
  asm volatile("ldmatrix.sync.aligned.m8n8.x4.shared.b16 {%0,%1,%2,%3}, [%4];" : "=r"(r[0]), "=r"(r[1]), "=r"(r[2]), "=r"(r[3]) : "r"(a) : "memory");
}
__device__ __forceinline__ void ldsm4t(uint32_t (&r)[4], uint32_t a) {
  asm volatile("ldmatrix.sync.aligned.m8n8.x4.trans.shared.b16 {%0,%1,%2,%3}, [%4];" : "=r"(r[0]), "=r"(r[1]), "=r"(r[2]), "=r"(r[3]) : "r"(a) : "memory");
}
__device__ __forceinline__ void ldsm2(uint32_t (&r)[2], uint32_t a) {
  asm volatile("ldmatrix.sync.aligned.m8n8.x2.shared.b16 {%0,%1}, [%2];" : "=r"(r[0]), "=r"(r[1]) : "r"(a) : "memory");
}

__device__ __forceinline__ uint4* mish_ptr(uint8_t* stp, int s, int i, int ct) {
  const int row = (ct >> 3) + 64 * (s & 1) + 32 * i;
  return reinterpret_cast<uint4*>(stp + (s >> 1) * 16384 + row * 128 + (((ct & 7) ^ (row & 7)) << 4));
}
__device__ __forceinline__ void mish_slice(uint8_t* stp, const float (&omr)[4], const uint4 bv, const uint4 (&v)[2], int s, int ct) {
#pragma unroll
  for (int i = 0; i < 2; i++) {
    const float om = (s & 1) ? omr[2 + i] : omr[i], om2 = -2.f * om;
    uint4 o;
    o.x = mish2(v[i].x, bv.x, om, om2);
    o.y = mish2(v[i].y, bv.y, om, om2);
    o.z = mish2(v[i].z, bv.z, om, om2);
    o.w = mish2(v[i].w, bv.w, om, om2);
    *mish_ptr(stp, s, i, ct) = o;
  }
}

__device__ __forceinline__ void warp_done(uint32_t bar, int lane) {
  fence_async_smem();
  __syncwarp();
  if (lane == 0) mbar_arrive(bar);
}

__global__ void __cluster_dims__(2, 1, 1) __launch_bounds__(NTHREADS, 1)
fused_kernel(const __grid_constant__ Maps maps, const __nv_bfloat16* __restrict__ b1,
             const __nv_bfloat16* __restrict__ gate_w, const uint8_t* __restrict__ wqkv_raw,
             const uint8_t* __restrict__ w2_raw, const uint8_t* __restrict__ wo_raw) {
  extern __shared__ uint8_t smem_raw[];
  const uint32_t ring = (s2u(smem_raw) + 1023) & ~1023u;
  const uint32_t bars = ring + MISC_OFF;
  uint8_t* const sp = smem_raw + (ring - s2u(smem_raw));
  const int tid = threadIdx.x, wgi = tid >> 7, warp = (tid >> 5) & 3, lane = tid & 31;
  const int cta = blockIdx.x;
  const bool regular = cta < NREG_CTAS;
  const int rb = cta & 15, j = cta >> 4;
  const int nw1 = j < 6 ? 4 : (j == 6 ? 3 : 0);
  const int w1_at0 = 4 * j;
  const int q1_at0 = j == 6 ? 0 : 1;
  const int q2_at0 = 5 + 3 * j;
  const int xrb = (cta - NREG_CTAS) * 4;
  const int rank = cta & 1, pr = cta >> 1;
  const int rb2 = pr & 15, nt = pr >> 4;

  if (tid == 0) {
    for (int i = 0; i < 6; i++) { mbar_init(bars + (B_FULL1 + i) * 8, 1); mbar_init(bars + (B_EMPTY1 + i) * 8, regular ? 11 : 8); }
    for (int i = 0; i < 4; i++) { mbar_init(bars + (B_FULL2 + i) * 8, 1); mbar_init(bars + (B_EMPTY2 + i) * 8, 8); }
    mbar_init(bars + B_STGFULL * 8, 1);
    mbar_init(bars + B_STGFREE * 8, regular ? 2 : 1);
    mbar_init(bars + B_GREADY * 8, 3);
    mbar_init(bars + B_ATTFULL * 8, 1);
    mbar_init(bars + B_PEERFREE * 8, 1);
    mbar_init(bars + B_PEERDATA * 8, 1);
    mbar_init(bars + B_HDONE * 8, 8);
    for (int i = 0; i < 3; i++) mbar_init(bars + (B_HD1 + i) * 8, 8);
    mbar_init(bars + B_ODONE * 8, 8);
    mbar_expect(bars + B_PEERDATA * 8, 40960);
    asm volatile("fence.mbarrier_init.release.cluster;" ::: "memory");
    asm volatile("fence.proxy.async;" ::: "memory");
    if (regular) {
      for (int k = 0; k < 4; k++) {
        uint32_t base = ring + k * SLOT1, fb = bars + (B_FULL1 + k) * 8;
        mbar_expect(fb, SLOT1);
        tma_load(base, &maps.x, fb, k * 64, rb * 128);
        for (int a = 0; a < 4; a++) {
          if (a < nw1) tma_load(base + 16384 + a * 8192, &maps.w1, fb, (w1_at0 + a) * 64, k * 64);
          else tma_load(base + 16384 + a * 8192, &maps.wqkv, fb, (q1_at0 + a - nw1) * 64, k * 64);
        }
      }
    }
  }
  if (tid == 32) {
    const CUtensorMap* mp = &maps.x;
    for (int i = 0; i < 12; i++) asm volatile("prefetch.tensormap [%0];" ::"l"(mp + i) : "memory");
  }
  if (tid == 64 && regular) {
    asm volatile("cp.async.bulk.prefetch.L2.global [%0], %1;" ::"l"(wqkv_raw + cta * 19200), "r"(19200) : "memory");
    asm volatile("cp.async.bulk.prefetch.L2.global [%0], %1;" ::"l"(w2_raw + cta * 17280), "r"(17280) : "memory");
    asm volatile("cp.async.bulk.prefetch.L2.global [%0], %1;" ::"l"(wo_raw + cta * 6400), "r"(6400) : "memory");
  }
  __syncthreads();
  asm volatile("barrier.cluster.arrive.release.aligned;" ::: "memory");

  if (wgi == 0) {
   asm volatile("setmaxnreg.dec.sync.aligned.u32 104;");
   const uint32_t stg = ring + STG_OFF;
   if (tid < 32) {
    if (tid == 0) {
      if (!regular) {
        int slot = 0;
        for (int i = 0; i < 40; i++) {
          mbar_wait(bars + (B_EMPTY1 + slot) * 8, ((i / 6) & 1) ^ 1);
          uint32_t base = ring + slot * SLOTX, fb = bars + (B_FULL1 + slot) * 8;
          const int t = i / 10, k = i - t * 10;
          mbar_expect(fb, SLOTX);
          tma_load(base, &maps.x, fb, k * 64, (xrb + t) * 128);
          tma_load(base + 16384, &maps.wqkv, fb, 29 * 64, k * 64);
          if (++slot == 6) slot = 0;
        }
      } else {
        for (int k = 4; k < 10; k++) {
          const int slot = k & 3;
          mbar_wait(bars + (B_EMPTY1 + slot) * 8, ((k >> 2) & 1) ^ 1);
          uint32_t base = ring + slot * SLOT1, fb = bars + (B_FULL1 + slot) * 8;
          mbar_expect(fb, SLOT1);
          tma_load(base, &maps.x, fb, k * 64, rb * 128);
          for (int a = 0; a < 4; a++) {
            if (a < nw1) tma_load(base + 16384 + a * 8192, &maps.w1, fb, (w1_at0 + a) * 64, k * 64);
            else tma_load(base + 16384 + a * 8192, &maps.wqkv, fb, (q1_at0 + a - nw1) * 64, k * 64);
          }
        }
        const int nh = rank == 0 ? 14 : 13, h0 = rank == 0 ? 0 : 14, o0 = rank == 0 ? 0 : 5;
        const int c0 = (nt & 1) ? 160 * nt + 32 : 160 * nt;
        const int c2 = (nt & 1) ? 160 * nt - 32 : 160 * nt + 128;
        for (int i = 0; i < 10 + nh + 5; i++) {
          const int slot = (i + 3) & 3;
          if (i < 4) {
            if (i == 0) { mbar_wait(bars + (B_EMPTY1 + 2) * 8, 1); mbar_wait(bars + (B_EMPTY1 + 3) * 8, 1); }
            else if (i == 1) mbar_wait(bars + (B_EMPTY1 + 0) * 8, 0);
            else if (i == 2) mbar_wait(bars + (B_EMPTY1 + 1) * 8, 0);
          } else mbar_wait(bars + (B_EMPTY2 + slot) * 8, ((i >> 2) & 1) ^ 1);
          uint32_t base = ring + slot * SLOT2, fb = bars + (B_FULL2 + slot) * 8;
          if (i < 10) {
            mbar_expect(fb, SLOT2);
            tma_load(base, &maps.x, fb, i * 64, rb * 128);
            for (int a = 0; a < 3; a++) tma_load(base + 16384 + a * 8192, &maps.wqkv, fb, (q2_at0 + a) * 64, i * 64);
          } else {
            const int p = i - 10;
            if (p == 0) { TS(16); flag_wait(&g_flags[(F_H + rb2) * FSTR], 7); TS(17); fence_async(); }
            if (p == nh) { TS(18); flag_wait(&g_flags[(F_O + rb2) * FSTR], 8); TS(19); fence_async(); }
            mbar_expect(fb, SLOT2);
            const bool hp = p < nh;
            const int kc = (hp ? h0 + p : o0 + p - nh) * 64;
            const CUtensorMap* ma = hp ? &maps.h : &maps.o;
            const CUtensorMap* mb = hp ? &maps.w2 : &maps.wo;
            tma_load(base, ma, fb, kc, rb2 * 128);
            tma_load(base + 16384, mb, fb, c0, kc);
            tma_load(base + 16384 + 8192, mb, fb, c0 + 64, kc);
            tma_load(base + 16384 + 16384, mb, fb, c2, kc);
          }
        }
        finish_reader();
      }
    }
    __syncwarp();
    asm volatile("barrier.cluster.wait.acquire.aligned;" ::: "memory");
   } else if (!regular) {
    asm volatile("barrier.cluster.wait.acquire.aligned;" ::: "memory");
    if (tid == 32) {
      for (int t = 0; t < 4; t++) {
        mbar_wait(bars + B_STGFULL * 8, t & 1);
        tma_store(&maps.qkv_st, stg, 29 * 64, (xrb + t) * 128);
        bulk_commit_wait();
        mbar_arrive(bars + B_STGFREE * 8);
        flag_add(&g_flags[(F_QKV + xrb + t) * FSTR]);
      }
    }
   } else {
    const int t = tid - 32;
    float* const sGp = reinterpret_cast<float*>(sp + SG_OFF);
    {
      const int ch = t & 7, r0 = t >> 3;
      float dot[11];
#pragma unroll
      for (int i = 0; i < 11; i++) dot[i] = 0.f;
      for (int k = 0; k < 10; k++) {
        uint4 w = __ldg(reinterpret_cast<const uint4*>(gate_w + k * 64 + ch * 8));
        mbar_wait(bars + (B_FULL1 + (k & 3)) * 8, (k >> 2) & 1);
        const uint8_t* abase = sp + (k & 3) * SLOT1;
        uint4 a[11];
#pragma unroll
        for (int i = 0; i < 11; i++) {
          int row = min(r0 + 12 * i, 127);
          a[i] = *reinterpret_cast<const uint4*>(abase + row * 128 + ((ch ^ (row & 7)) << 4));
        }
#pragma unroll
        for (int i = 0; i < 11; i++)
          dot[i] += bf_lo(a[i].x) * bf_lo(w.x) + bf_hi(a[i].x) * bf_hi(w.x) + bf_lo(a[i].y) * bf_lo(w.y) + bf_hi(a[i].y) * bf_hi(w.y)
                  + bf_lo(a[i].z) * bf_lo(w.z) + bf_hi(a[i].z) * bf_hi(w.z) + bf_lo(a[i].w) * bf_lo(w.w) + bf_hi(a[i].w) * bf_hi(w.w);
#pragma unroll
        for (int i = 0; i < 11; i++) asm volatile("" : "+f"(dot[i])::"memory");
        __syncwarp();
        if (lane == 0) mbar_arrive(bars + (B_EMPTY1 + (k & 3)) * 8);
      }
#pragma unroll
      for (int i = 0; i < 11; i++) {
        float d = dot[i];
        d += __shfl_xor_sync(0xffffffffu, d, 1); d += __shfl_xor_sync(0xffffffffu, d, 2); d += __shfl_xor_sync(0xffffffffu, d, 4);
        int row = r0 + 12 * i;
        if (ch == 0 && row < 128) sGp[row] = rcpf(1.f + ex2f(-1.4426950408889634f * d));
      }
      __syncwarp();
      if (lane == 0) mbar_arrive(bars + B_GREADY * 8);
      if (t == 0) TS(8);
    }
    asm volatile("barrier.cluster.wait.acquire.aligned;" ::: "memory");
    if (t == 32) {
      for (int a = 0; a < nw1; a++) {
        mbar_wait(bars + (a == 0 ? B_HDONE : B_HD1 + a - 1) * 8, 0);
        tma_store(&maps.h, stg + a * 16384, (w1_at0 + a) * 64, rb * 128);
      }
      if (nw1 > 0) { bulk_commit_wait(); flag_add(&g_flags[(F_H + rb) * FSTR]); }
      mbar_arrive(bars + B_STGFREE * 8);
      TS(10);
      mbar_wait(bars + B_ODONE * 8, 0);
      TS(28);
      tma_store3(&maps.o_st, stg, 80 * j, rb * 64);
      bulk_commit_wait();
      flag_add(&g_flags[(F_O + rb) * FSTR]);
      mbar_arrive_cl(mapa(bars + B_PEERFREE * 8, rank ^ 1));
      TS(15);
    } else if (t == 0) {
      mbar_wait(bars + B_STGFULL * 8, 0);
      if (nw1 < 4) {
        for (int a = nw1; a < 4; a++) tma_store(&maps.qkv_st, stg + a * 16384, (q1_at0 + a - nw1) * 64, rb * 128);
        bulk_commit_wait();
        flag_add(&g_flags[(F_QKV + rb) * FSTR]);
      }
      mbar_arrive(bars + B_STGFREE * 8);
      mbar_wait(bars + B_STGFULL * 8, 1);
      TS(11);
      for (int a = 0; a < 3; a++) tma_store(&maps.qkv_st, stg + a * 16384, (q2_at0 + a) * 64, rb * 128);
      bulk_commit_wait();
      flag_add(&g_flags[(F_QKV + rb) * FSTR]);
      TS(12);
      flag_wait(&g_flags[(F_QKV + rb) * FSTR], 11);
      if (rb > 0) flag_wait(&g_flags[(F_QKV + rb - 1) * FSTR], 11);
      fence_async();
      TS(13);
      uint32_t fb = bars + B_ATTFULL * 8;
      mbar_expect(fb, 128 * 160 + 2 * 142 * 160);
      tma_load3(stg, &maps.qkv_ldq, fb, 80 * j, rb * 64);
      tma_load3(stg + ATT_K_OFF, &maps.qkv_ldkv, fb, 640 + 80 * j, rb * 64 - 7);
      tma_load3(stg + ATT_V_OFF, &maps.qkv_ldkv, fb, 1280 + 80 * j, rb * 64 - 7);
      finish_reader();
    }
   }
  } else {
    asm volatile("setmaxnreg.inc.sync.aligned.u32 200;");
    const int wg = wgi - 1;
    int slot = 0, cnt = 0;
    if (tid == 128) TS(0);
    const int ct = tid - 128;
    uint8_t* const stp = sp + STG_OFF;
    const float* const sGp = reinterpret_cast<const float*>(sp + SG_OFF);
    auto nobg = [](int) {};
    if (!regular) {
      asm volatile("barrier.cluster.wait.acquire.aligned;" ::: "memory");
      for (int tl = 0; tl < 4; tl++) {
        float acc[32];
        tile_loop<64, 6, SLOTX>(acc, ring, bars + B_FULL1 * 8, bars + B_EMPTY1 * 8, slot, cnt, wg, lane, nobg);
        if (tl > 0) mbar_wait(bars + B_STGFREE * 8, (tl - 1) & 1);
        dump_tile<64>(acc, ring + STG_OFF, wg, warp, lane);
        fence_async_smem();
        named_bar(2, 256);
        if (tid == 128) mbar_arrive(bars + B_STGFULL * 8);
      }
    } else {
      uint4 bv[4];
#pragma unroll
      for (int a = 0; a < 4; a++) bv[a] = __ldg(reinterpret_cast<const uint4*>(b1 + min(w1_at0 + a, 26) * 64 + (ct & 7) * 8));
      {
        float acc[128];
        tile_loop<256, 4, SLOT1>(acc, ring, bars + B_FULL1 * 8, bars + B_EMPTY1 * 8, slot, cnt, wg, lane, nobg);
        if (tid == 128) TS(1);
        named_bar(2, 256);
        dump_tile<256>(acc, ring + STG_OFF, wg, warp, lane);
        fence_async_smem();
        named_bar(2, 256);
      }
      if (tid == 128) { mbar_arrive(bars + B_STGFULL * 8); TS(2); }
      asm volatile("barrier.cluster.wait.acquire.aligned;" ::: "memory");
      slot = 3; cnt = 0;
      {
        float acc[96];
        float omr[4];
        uint4 vn[2];
        tile_loop<192, 4, SLOT2>(acc, ring, bars + B_FULL2 * 8, bars + B_EMPTY2 * 8, slot, cnt, wg, lane, [&](int k1) {
          const int k = k1 - 1;
          if (k == 0) {
            mbar_wait(bars + B_GREADY * 8, 0);
#pragma unroll
            for (int i = 0; i < 4; i++) omr[i] = 1.f - sGp[(ct >> 3) + 32 * i];
            vn[0] = *mish_ptr(stp, 0, 0, ct); vn[1] = *mish_ptr(stp, 0, 1, ct);
          }
          if (k >= 0 && k < nw1) {
            const uint4 b = k == 0 ? bv[0] : k == 1 ? bv[1] : k == 2 ? bv[2] : bv[3];
#pragma unroll 1
            for (int sl = 2 * k; sl < 2 * k + 2; sl++) {
              const uint4 v[2] = {vn[0], vn[1]};
              if (sl + 1 < 2 * nw1) { vn[0] = *mish_ptr(stp, sl + 1, 0, ct); vn[1] = *mish_ptr(stp, sl + 1, 1, ct); }
              mish_slice(stp, omr, b, v, sl, ct);
            }
            warp_done(bars + (k == 0 ? B_HDONE : B_HD1 + k - 1) * 8, lane);
          }
        });
        if (tid == 128) TS(3);
        mbar_wait(bars + B_STGFREE * 8, 0);
        named_bar(2, 256);
        dump_tile<192>(acc, ring + STG_OFF, wg, warp, lane);
        fence_async_smem();
        named_bar(2, 256);
      }
      if (tid == 128) { mbar_arrive(bars + B_STGFULL * 8); TS(4); }

      const int g8 = lane >> 2, c4 = lane & 3;
      const int par = warp & 1, P0 = ((wg * 4 + warp) >> 1) * 16;
      const uint32_t stq = ring + STG_OFF + par * (64 * 160);
      const uint32_t stk = ring + STG_OFF + ATT_K_OFF + par * (71 * 160);
      const uint32_t stv = ring + STG_OFF + ATT_V_OFF + par * (71 * 160);
      int ast = 0;
      auto att_step = [&]() {
        if (tid == 128 && ast == 0) TS(22);
        const bool oddh = (ast & 1) != 0;
        const int hoffb = ast * 40 - (oddh ? 8 : 0);
        uint32_t qa[4], qb[2];
        {
          const uint32_t qrow = stq + (P0 + (lane & 7) + ((lane >> 3) & 1) * 8) * 160 + hoffb;
          ldsm4(qa, qrow + (lane >> 4) * 16);
          ldsm2(qb, qrow + 32);
          if (oddh) { if (c4 < 2) { qa[0] = 0u; qa[1] = 0u; } }
          else if (c4 >= 2) { qb[0] = 0u; qb[1] = 0u; }
        }
        const int chunk = min(lane >> 3, 2);
        float sfr[3][4];
#pragma unroll
        for (int n = 0; n < 3; n++) {
          uint32_t kb[4];
          ldsm4(kb, stk + min(P0 + 8 * n + (lane & 7), 70) * 160 + hoffb + chunk * 16);
          sfr[n][0] = sfr[n][1] = sfr[n][2] = sfr[n][3] = 0.f;
          mma16816(sfr[n], qa[0], qa[1], qa[2], qa[3], kb[0], kb[1]);
          mma16816(sfr[n], qb[0], qb[1], 0u, 0u, kb[2], 0u);
        }
        uint32_t vb[3][4];
#pragma unroll
        for (int d = 0; d < 3; d++) ldsm4t(vb[d], stv + min(P0 + 8 * chunk + (lane & 7), 70) * 160 + hoffb + d * 16);
        const float sc = 0.22360679774997896f * 1.4426950408889634f;
        const int tmin = 7 - (rb * 64 + P0);
        float mx0 = -3.0e38f, mx1 = -3.0e38f;
#pragma unroll
        for (int n = 0; n < 3; n++) {
#pragma unroll
          for (int e = 0; e < 2; e++) {
            const int t = 8 * n + 2 * c4 + e;
            sfr[n][e] = (t >= g8 && t <= g8 + 7 && t >= tmin) ? sfr[n][e] * sc : -3.0e38f;
            sfr[n][2 + e] = (t >= g8 + 8 && t <= g8 + 15 && t >= tmin) ? sfr[n][2 + e] * sc : -3.0e38f;
            mx0 = fmaxf(mx0, sfr[n][e]); mx1 = fmaxf(mx1, sfr[n][2 + e]);
          }
        }
        mx0 = fmaxf(mx0, __shfl_xor_sync(0xffffffffu, mx0, 1)); mx1 = fmaxf(mx1, __shfl_xor_sync(0xffffffffu, mx1, 1));
        mx0 = fmaxf(mx0, __shfl_xor_sync(0xffffffffu, mx0, 2)); mx1 = fmaxf(mx1, __shfl_xor_sync(0xffffffffu, mx1, 2));
        float s0 = 0.f, s1 = 0.f;
#pragma unroll
        for (int n = 0; n < 3; n++) {
#pragma unroll
          for (int e = 0; e < 2; e++) {
            sfr[n][e] = ex2f(sfr[n][e] - mx0); sfr[n][2 + e] = ex2f(sfr[n][2 + e] - mx1);
            s0 += sfr[n][e]; s1 += sfr[n][2 + e];
          }
        }
        s0 += __shfl_xor_sync(0xffffffffu, s0, 1); s1 += __shfl_xor_sync(0xffffffffu, s1, 1);
        s0 += __shfl_xor_sync(0xffffffffu, s0, 2); s1 += __shfl_xor_sync(0xffffffffu, s1, 2);
        const uint32_t p0 = pack_bf16(sfr[0][0], sfr[0][1]), p1 = pack_bf16(sfr[0][2], sfr[0][3]);
        const uint32_t p2 = pack_bf16(sfr[1][0], sfr[1][1]), p3 = pack_bf16(sfr[1][2], sfr[1][3]);
        const uint32_t p4 = pack_bf16(sfr[2][0], sfr[2][1]), p5 = pack_bf16(sfr[2][2], sfr[2][3]);
        const float f0 = sGp[2 * (P0 + g8) + par] * rcpf(s0), f1 = sGp[2 * (P0 + g8 + 8) + par] * rcpf(s1);
        float ofr[3][4];
#pragma unroll
        for (int d = 0; d < 3; d++) {
          ofr[d][0] = ofr[d][1] = ofr[d][2] = ofr[d][3] = 0.f;
          mma16816(ofr[d], p0, p1, p2, p3, vb[d][0], vb[d][1]);
          mma16816(ofr[d], p4, p5, 0u, 0u, vb[d][2], 0u);
        }
        __syncwarp();
        uint8_t* op = stp + par * (64 * 160) + (P0 + g8) * 160 + hoffb + c4 * 4;
#pragma unroll
        for (int d = 0; d < 3; d++) {
          const bool ok = oddh ? (d > 0 || c4 >= 2) : (d < 2 || c4 < 2);
          if (ok) {
            *reinterpret_cast<uint32_t*>(op + d * 16) = pack_bf16(ofr[d][0] * f0, ofr[d][1] * f0);
            *reinterpret_cast<uint32_t*>(op + 8 * 160 + d * 16) = pack_bf16(ofr[d][2] * f1, ofr[d][3] * f1);
          }
        }
        if (ast == 3) {
          warp_done(bars + B_ODONE * 8, lane);
          if (tid == 128) TS(26);
        }
        ast++;
      };
      const int nh = rank == 0 ? 14 : 13;
      float accA[64], accB[16];
      zero_acc(accA); zero_acc(accB);
      const uint64_t hoff = 1024 + ((nt & 1) ? 4 : 0);
      mainloop<4, SLOT2>(ring, bars + B_FULL2 * 8, bars + B_EMPTY2 * 8, slot, cnt, nh + 5, wg, lane, [&](uint64_t da, uint64_t db) {
#pragma unroll
        for (int kk = 0; kk < 4; kk++) {
          wgmma_n128(accA, da + kk * 2, db + kk * 128, 1);
          wgmma_n32(accB, da + kk * 2, db + hoff + kk * 128, 1);
        }
      }, [&](int k) {
        if (k == K_ATT) {
          mbar_wait(bars + B_ATTFULL * 8, 0);
          wg_wait<0>();
#pragma unroll 2
          for (int hh = 0; hh < 4; hh++) att_step();
        }
      });
      pin_acc(accA); pin_acc(accB);
      float acc[80];
#pragma unroll
      for (int i = 0; i < 64; i++) acc[i] = accA[i];
#pragma unroll
      for (int i = 0; i < 16; i++) acc[64 + i] = accB[i];
      const uint32_t peer = rank ^ 1;
      if (tid == 128) TS(5);
      mbar_wait_cl(bars + B_PEERFREE * 8, 0);
      const uint32_t rdst = mapa(ring + STG_OFF + ATT_K_OFF + ct * 16, peer);
      const uint32_t rbar = mapa(bars + B_PEERDATA * 8, peer);
      const bool odd = (nt & 1) != 0;
      float keep[40], snd[40];
#pragma unroll
      for (int i = 0; i < 10; i++) {
        const int be0 = i, be1 = 10 + i;
        const int bo0 = i < 4 ? 16 + i : i - 4, bo1 = 6 + i;
#pragma unroll
        for (int e = 0; e < 4; e++) {
          const float r0 = odd ? acc[4 * bo0 + e] : acc[4 * be0 + e];
          const float r1 = odd ? acc[4 * bo1 + e] : acc[4 * be1 + e];
          keep[4 * i + e] = rank == 0 ? r0 : r1;
          snd[4 * i + e] = rank == 0 ? r1 : r0;
        }
      }
#pragma unroll
      for (int i = 0; i < 10; i++)
        asm volatile("st.async.shared::cluster.mbarrier::complete_tx::bytes.v4.f32 [%0], {%1,%2,%3,%4}, [%5];"
                     ::"r"(rdst + i * 4096), "f"(snd[4 * i]), "f"(snd[4 * i + 1]), "f"(snd[4 * i + 2]), "f"(snd[4 * i + 3]), "r"(rbar) : "memory");
      mbar_wait_cl(bars + B_PEERDATA * 8, 0);
      if (tid == 128) TS(6);
      uint8_t* orow = sp + (wg * 64 + warp * 16 + (lane >> 2)) * 160 + (lane & 3) * 4;
#pragma unroll
      for (int i = 0; i < 10; i++) {
        const float4 v = *reinterpret_cast<const float4*>(stp + ATT_K_OFF + ct * 16 + i * 4096);
        *reinterpret_cast<uint32_t*>(orow + i * 16) = pack_bf16(v.x + keep[4 * i], v.y + keep[4 * i + 1]);
        *reinterpret_cast<uint32_t*>(orow + 8 * 160 + i * 16) = pack_bf16(v.z + keep[4 * i + 2], v.w + keep[4 * i + 3]);
      }
      fence_async_smem();
      named_bar(2, 256);
      if (tid == 128) {
        tma_store(&maps.out_st, ring, 160 * nt + 80 * rank, rb2 * 128);
        asm volatile("cp.async.bulk.commit_group;" ::: "memory");
        asm volatile("cp.async.bulk.wait_group.read 0;" ::: "memory");
      }
      if (tid == 128) TS(7);
    }
  }
}

typedef CUresult (*EncFn)(CUtensorMap*, CUtensorMapDataType, cuuint32_t, void*, const cuuint64_t*, const cuuint64_t*,
                          const cuuint32_t*, const cuuint32_t*, CUtensorMapInterleave, CUtensorMapSwizzle,
                          CUtensorMapL2promotion, CUtensorMapFloatOOBfill);

void make_map(EncFn enc, CUtensorMap* m, const void* p, int cols, int rows, int bc, int br, bool swz) {
  cuuint64_t d[2] = {(cuuint64_t)cols, (cuuint64_t)rows};
  cuuint64_t s[1] = {(cuuint64_t)cols * 2};
  cuuint32_t b[2] = {(cuuint32_t)bc, (cuuint32_t)br};
  cuuint32_t e[2] = {1, 1};
  enc(m, CU_TENSOR_MAP_DATA_TYPE_BFLOAT16, 2, const_cast<void*>(p), d, s, b, e, CU_TENSOR_MAP_INTERLEAVE_NONE,
      swz ? CU_TENSOR_MAP_SWIZZLE_128B : CU_TENSOR_MAP_SWIZZLE_NONE, CU_TENSOR_MAP_L2_PROMOTION_L2_128B,
      CU_TENSOR_MAP_FLOAT_OOB_FILL_NONE);
}

void make_map3(EncFn enc, CUtensorMap* m, const void* p, int cols, int rows, int bc, int bpairs) {
  cuuint64_t d[3] = {(cuuint64_t)cols, (cuuint64_t)rows / 2, 2};
  cuuint64_t s[2] = {(cuuint64_t)cols * 4, (cuuint64_t)cols * 2};
  cuuint32_t b[3] = {(cuuint32_t)bc, (cuuint32_t)bpairs, 2};
  cuuint32_t e[3] = {1, 1, 1};
  enc(m, CU_TENSOR_MAP_DATA_TYPE_BFLOAT16, 3, const_cast<void*>(p), d, s, b, e, CU_TENSOR_MAP_INTERLEAVE_NONE,
      CU_TENSOR_MAP_SWIZZLE_NONE, CU_TENSOR_MAP_L2_PROMOTION_L2_128B, CU_TENSOR_MAP_FLOAT_OOB_FILL_NONE);
}

}

extern "C" void kernel_launch(void* const* d_in, const int* in_sizes, int n_in, void* d_out, int out_size) {
  (void)in_sizes; (void)n_in; (void)out_size;
  static Maps maps;
  static const void* seen[9] = {nullptr};
  bool same = seen[8] == d_out;
  for (int i = 0; i < 8; i++) same = same && seen[i] == d_in[i];
  if (!same) {
    for (int i = 0; i < 8; i++) seen[i] = d_in[i];
    seen[8] = d_out;
    EncFn enc = nullptr;
    cudaDriverEntryPointQueryResult q;
    cudaGetDriverEntryPoint("cuTensorMapEncodeTiled", (void**)&enc, cudaEnableDefault, &q);
    void *ph, *po, *pq;
    cudaGetSymbolAddress(&ph, g_h);
    cudaGetSymbolAddress(&po, g_o);
    cudaGetSymbolAddress(&pq, g_qkv);
    make_map(enc, &maps.x, d_in[0], DM, SEQ, 64, 128, true);
    make_map(enc, &maps.wqkv, d_in[1], QKVN, DM, 64, 64, true);
    make_map(enc, &maps.wo, d_in[2], DM, DM, 64, 64, true);
    make_map(enc, &maps.w1, d_in[4], FF, DM, 64, 64, true);
    make_map(enc, &maps.w2, d_in[6], DM, FF, 64, 64, true);
    make_map(enc, &maps.h, ph, FF, SEQ, 64, 128, true);
    make_map(enc, &maps.o, po, DM, SEQ, 64, 128, true);
    make_map(enc, &maps.qkv_st, pq, QKVN, SEQ, 64, 128, true);
    make_map3(enc, &maps.qkv_ldq, pq, QKVN, SEQ, 80, 64);
    make_map3(enc, &maps.qkv_ldkv, pq, QKVN, SEQ, 80, 71);
    make_map3(enc, &maps.o_st, po, DM, SEQ, 80, 64);
    make_map(enc, &maps.out_st, d_out, DM, SEQ, 80, 128, false);
    cudaFuncSetAttribute(fused_kernel, cudaFuncAttributeMaxDynamicSharedMemorySize, SMEM_ALLOC);
  }
  fused_kernel<<<NCTAS, NTHREADS, SMEM_ALLOC>>>(maps, (const __nv_bfloat16*)d_in[5], (const __nv_bfloat16*)d_in[7],
                                               (const uint8_t*)d_in[1], (const uint8_t*)d_in[6], (const uint8_t*)d_in[2]);
}
```

```cpp
#include <cuda_runtime.h>
#include <cuda.h>
#include <cuda_bf16.h>
#include <stdint.h>

namespace {

constexpr int SEQ = 2048, DM = 640, FF = 1728, QKVN = 1920;
constexpr int NTHREADS = 384;
constexpr int NREG_CTAS = 128;
constexpr int NCTAS = 132;

#define K_ATT 7

constexpr int RING_BYTES = 163840;
constexpr int SLOT1 = 49152;
constexpr int SLOT2 = 40960;
constexpr int SLOTX = 24576;
constexpr int STG_OFF = RING_BYTES;
constexpr int STG_BYTES = 66048;
constexpr int ATT_K_OFF = 20480;
constexpr int ATT_V_OFF = 43264;
constexpr int MISC_OFF = STG_OFF + STG_BYTES;
constexpr int SG_OFF = MISC_OFF + 256;
constexpr int SMEM_USED = SG_OFF + 1024;
constexpr int SMEM_ALLOC = SMEM_USED + 1024;

enum { B_FULL1 = 0, B_EMPTY1 = 6, B_FULL2 = 12, B_EMPTY2 = 16,
       B_STGFULL = 20, B_GREADY = 21, B_ATTFULL = 22, B_PEERFREE = 23, B_PEERDATA = 24, B_HDONE = 25, B_ODONE = 26,
       B_STGFREE = 27, B_HD1 = 28, B_COUNT = 31 };

enum { F_H = 0, F_QKV = 16, F_O = 32, F_FIN = 48 };
constexpr int FSTR = 32;

__device__ __nv_bfloat16 g_h[SEQ * FF];
__device__ __nv_bfloat16 g_o[SEQ * DM];
__device__ __nv_bfloat16 g_qkv[SEQ * QKVN];
__device__ unsigned g_flags[64 * 32];

struct Maps { CUtensorMap x, wqkv, w1, w2, wo, h, o, qkv_st, qkv_ldq, qkv_ldkv, o_st, out_st; };

__device__ __forceinline__ uint32_t s2u(const void* p) { return (uint32_t)__cvta_generic_to_shared(p); }
__device__ __forceinline__ void mbar_init(uint32_t b, int c) { asm volatile("mbarrier.init.shared::cta.b64 [%0], %1;" ::"r"(b), "r"(c)); }
__device__ __forceinline__ void mbar_expect(uint32_t b, int bytes) { asm volatile("mbarrier.arrive.expect_tx.shared::cta.b64 _, [%0], %1;" ::"r"(b), "r"(bytes) : "memory"); }
__device__ __forceinline__ void mbar_arrive(uint32_t b) { asm volatile("mbarrier.arrive.shared::cta.b64 _, [%0];" ::"r"(b) : "memory"); }
__device__ __forceinline__ bool mbar_try(uint32_t b, int par) {
  uint32_t ok;
  asm volatile("{\n.reg .pred p;\nmbarrier.try_wait.parity.shared::cta.b64 p, [%1], %2;\nselp.u32 %0, 1, 0, p;\n}" : "=r"(ok) : "r"(b), "r"(par) : "memory");
  return ok != 0;
}
__device__ __forceinline__ bool mbar_test(uint32_t b, int par) {
  uint32_t ok;
  asm volatile("{\n.reg .pred p;\nmbarrier.test_wait.parity.shared::cta.b64 p, [%1], %2;\nselp.u32 %0, 1, 0, p;\n}" : "=r"(ok) : "r"(b), "r"(par) : "memory");
  return ok != 0;
}
__device__ __forceinline__ void mbar_wait(uint32_t b, int par) {
  uint32_t n = 0;
  while (!mbar_try(b, par)) { if (++n > (1u << 22)) __trap(); }
}
__device__ __forceinline__ bool mbar_try_cl(uint32_t b, int par) {
  uint32_t ok;
  asm volatile("{\n.reg .pred p;\nmbarrier.try_wait.parity.acquire.cluster.shared::cta.b64 p, [%1], %2;\nselp.u32 %0, 1, 0, p;\n}" : "=r"(ok) : "r"(b), "r"(par) : "memory");
  return ok != 0;
}
__device__ __forceinline__ void mbar_wait_cl(uint32_t b, int par) {
  uint32_t n = 0;
  while (!mbar_try_cl(b, par)) { if (++n > (1u << 22)) __trap(); }
}
__device__ __forceinline__ uint32_t mapa(uint32_t a, uint32_t cta) { uint32_t r; asm volatile("mapa.shared::cluster.u32 %0, %1, %2;" : "=r"(r) : "r"(a), "r"(cta)); return r; }
__device__ __forceinline__ void mbar_arrive_cl(uint32_t remote) { asm volatile("mbarrier.arrive.release.cluster.shared::cluster.b64 _, [%0];" ::"r"(remote) : "memory"); }
__device__ __forceinline__ void tma_load(uint32_t dst, const CUtensorMap* m, uint32_t bar, int c0, int c1) {
  asm volatile("cp.async.bulk.tensor.2d.shared::cluster.global.mbarrier::complete_tx::bytes [%0], [%1, {%3,%4}], [%2];" ::"r"(dst), "l"(m), "r"(bar), "r"(c0), "r"(c1) : "memory");
}
__device__ __forceinline__ void tma_load3(uint32_t dst, const CUtensorMap* m, uint32_t bar, int c0, int c1) {
  asm volatile("cp.async.bulk.tensor.3d.shared::cluster.global.mbarrier::complete_tx::bytes [%0], [%1, {%3,%4,%5}], [%2];" ::"r"(dst), "l"(m), "r"(bar), "r"(c0), "r"(c1), "r"(0) : "memory");
}
__device__ __forceinline__ void tma_store3(const CUtensorMap* m, uint32_t src, int c0, int c1) {
  asm volatile("cp.async.bulk.tensor.3d.global.shared::cta.bulk_group [%0, {%2,%3,%4}], [%1];" ::"l"(m), "r"(src), "r"(c0), "r"(c1), "r"(0) : "memory");
}
__device__ __forceinline__ void tma_store(const CUtensorMap* m, uint32_t src, int c0, int c1) {
  asm volatile("cp.async.bulk.tensor.2d.global.shared::cta.bulk_group [%0, {%2,%3}], [%1];" ::"l"(m), "r"(src), "r"(c0), "r"(c1) : "memory");
}
__device__ __forceinline__ void fence_async() { asm volatile("fence.proxy.async.global;" ::: "memory"); }
__device__ __forceinline__ void fence_async_smem() { asm volatile("fence.proxy.async.shared::cta;" ::: "memory"); }
__device__ __forceinline__ void wg_fence() { asm volatile("wgmma.fence.sync.aligned;" ::: "memory"); }
__device__ __forceinline__ void wg_commit() { asm volatile("wgmma.commit_group.sync.aligned;" ::: "memory"); }
template <int N> __device__ __forceinline__ void wg_wait() { asm volatile("wgmma.wait_group.sync.aligned %0;" ::"n"(N) : "memory"); }
__device__ __forceinline__ void named_bar(int id, int n) { asm volatile("bar.sync %0, %1;" ::"r"(id), "r"(n) : "memory"); }
__device__ __forceinline__ unsigned ld_rlx(const unsigned* p) { unsigned v; asm volatile("ld.relaxed.gpu.global.u32 %0, [%1];" : "=r"(v) : "l"(p) : "memory"); return v; }
__device__ __forceinline__ void flag_add(unsigned* p) { asm volatile("red.relaxed.gpu.global.add.u32 [%0], 1;" ::"l"(p) : "memory"); }
__device__ __forceinline__ void flag_wait(const unsigned* p, unsigned target) {
  uint32_t n = 0;
  while (ld_rlx(p) < target) { __nanosleep(32); if (++n > (1u << 20)) __trap(); }
}
__device__ __forceinline__ void bulk_commit_wait() {
  asm volatile("cp.async.bulk.commit_group;" ::: "memory");
  asm volatile("cp.async.bulk.wait_group 0;" ::: "memory");
}
__device__ __forceinline__ void finish_reader() {
  unsigned old = atomicAdd(&g_flags[F_FIN * FSTR], 1u);
  if (old == 2 * NREG_CTAS - 1) {
    for (int i = 0; i <= F_FIN; i++) g_flags[i * FSTR] = 0;
  }
}
__device__ __forceinline__ uint32_t pack_bf16(float a, float b) { __nv_bfloat162 t = __floats2bfloat162_rn(a, b); return *reinterpret_cast<uint32_t*>(&t); }
__device__ __forceinline__ float bf_lo(uint32_t v) { return __uint_as_float(v << 16); }
__device__ __forceinline__ float bf_hi(uint32_t v) { return __uint_as_float(v & 0xffff0000u); }

__device__ __forceinline__ uint64_t desc_a(uint32_t a) { return (uint64_t)((a & 0x3FFFF) >> 4) | (1ull << 16) | (64ull << 32) | (1ull << 62); }
__device__ __forceinline__ uint64_t desc_b(uint32_t a) { return (uint64_t)((a & 0x3FFFF) >> 4) | (512ull << 16) | (64ull << 32) | (1ull << 62); }

__device__ __forceinline__ void wgmma_n256(float (&d)[128], uint64_t da, uint64_t db, int sc) {
  asm volatile("{\n.reg .pred p;\nsetp.ne.b32 p, %130, 0;\n"
    "wgmma.mma_async.sync.aligned.m64n256k16.f32.bf16.bf16 {%0, %1, %2, %3, %4, %5, %6, %7, %8, %9, %10, %11, %12, %13, %14, %15, %16, %17, %18, %19, %20, %21, %22, %23, %24, %25, %26, %27, %28, %29, %30, %31, %32, %33, %34, %35, %36, %37, %38, %39, %40, %41, %42, %43, %44, %45, %46, %47, %48, %49, %50, %51, %52, %53, %54, %55, %56, %57, %58, %59, %60, %61, %62, %63, %64, %65, %66, %67, %68, %69, %70, %71, %72, %73, %74, %75, %76, %77, %78, %79, %80, %81, %82, %83, %84, %85, %86, %87, %88, %89, %90, %91, %92, %93, %94, %95, %96, %97, %98, %99, %100, %101, %102, %103, %104, %105, %106, %107, %108, %109, %110, %111, %112, %113, %114, %115, %116, %117, %118, %119, %120, %121, %122, %123, %124, %125, %126, %127}, %128, %129, p, 1, 1, 0, 1;\n}\n"
    : "+f"(d[0]), "+f"(d[1]), "+f"(d[2]), "+f"(d[3]), "+f"(d[4]), "+f"(d[5]), "+f"(d[6]), "+f"(d[7]), "+f"(d[8]), "+f"(d[9]), "+f"(d[10]), "+f"(d[11]), "+f"(d[12]), "+f"(d[13]), "+f"(d[14]), "+f"(d[15]), "+f"(d[16]), "+f"(d[17]), "+f"(d[18]), "+f"(d[19]), "+f"(d[20]), "+f"(d[21]), "+f"(d[22]), "+f"(d[23]), "+f"(d[24]), "+f"(d[25]), "+f"(d[26]), "+f"(d[27]), "+f"(d[28]), "+f"(d[29]), "+f"(d[30]), "+f"(d[31]), "+f"(d[32]), "+f"(d[33]), "+f"(d[34]), "+f"(d[35]), "+f"(d[36]), "+f"(d[37]), "+f"(d[38]), "+f"(d[39]), "+f"(d[40]), "+f"(d[41]), "+f"(d[42]), "+f"(d[43]), "+f"(d[44]), "+f"(d[45]), "+f"(d[46]), "+f"(d[47]), "+f"(d[48]), "+f"(d[49]), "+f"(d[50]), "+f"(d[51]), "+f"(d[52]), "+f"(d[53]), "+f"(d[54]), "+f"(d[55]), "+f"(d[56]), "+f"(d[57]), "+f"(d[58]), "+f"(d[59]), "+f"(d[60]), "+f"(d[61]), "+f"(d[62]), "+f"(d[63]), "+f"(d[64]), "+f"(d[65]), "+f"(d[66]), "+f"(d[67]), "+f"(d[68]), "+f"(d[69]), "+f"(d[70]), "+f"(d[71]), "+f"(d[72]), "+f"(d[73]), "+f"(d[74]), "+f"(d[75]), "+f"(d[76]), "+f"(d[77]), "+f"(d[78]), "+f"(d[79]), "+f"(d[80]), "+f"(d[81]), "+f"(d[82]), "+f"(d[83]), "+f"(d[84]), "+f"(d[85]), "+f"(d[86]), "+f"(d[87]), "+f"(d[88]), "+f"(d[89]), "+f"(d[90]), "+f"(d[91]), "+f"(d[92]), "+f"(d[93]), "+f"(d[94]), "+f"(d[95]), "+f"(d[96]), "+f"(d[97]), "+f"(d[98]), "+f"(d[99]), "+f"(d[100]), "+f"(d[101]), "+f"(d[102]), "+f"(d[103]), "+f"(d[104]), "+f"(d[105]), "+f"(d[106]), "+f"(d[107]), "+f"(d[108]), "+f"(d[109]), "+f"(d[110]), "+f"(d[111]), "+f"(d[112]), "+f"(d[113]), "+f"(d[114]), "+f"(d[115]), "+f"(d[116]), "+f"(d[117]), "+f"(d[118]), "+f"(d[119]), "+f"(d[120]), "+f"(d[121]), "+f"(d[122]), "+f"(d[123]), "+f"(d[124]), "+f"(d[125]), "+f"(d[126]), "+f"(d[127])
    : "l"(da), "l"(db), "r"(sc));
}
__device__ __forceinline__ void wgmma_n192(float (&d)[96], uint64_t da, uint64_t db, int sc) {
  asm volatile("{\n.reg .pred p;\nsetp.ne.b32 p, %98, 0;\n"
    "wgmma.mma_async.sync.aligned.m64n192k16.f32.bf16.bf16 {%0, %1, %2, %3, %4, %5, %6, %7, %8, %9, %10, %11, %12, %13, %14, %15, %16, %17, %18, %19, %20, %21, %22, %23, %24, %25, %26, %27, %28, %29, %30, %31, %32, %33, %34, %35, %36, %37, %38, %39, %40, %41, %42, %43, %44, %45, %46, %47, %48, %49, %50, %51, %52, %53, %54, %55, %56, %57, %58, %59, %60, %61, %62, %63, %64, %65, %66, %67, %68, %69, %70, %71, %72, %73, %74, %75, %76, %77, %78, %79, %80, %81, %82, %83, %84, %85, %86, %87, %88, %89, %90, %91, %92, %93, %94, %95}, %96, %97, p, 1, 1, 0, 1;\n}\n"
    : "+f"(d[0]), "+f"(d[1]), "+f"(d[2]), "+f"(d[3]), "+f"(d[4]), "+f"(d[5]), "+f"(d[6]), "+f"(d[7]), "+f"(d[8]), "+f"(d[9]), "+f"(d[10]), "+f"(d[11]), "+f"(d[12]), "+f"(d[13]), "+f"(d[14]), "+f"(d[15]), "+f"(d[16]), "+f"(d[17]), "+f"(d[18]), "+f"(d[19]), "+f"(d[20]), "+f"(d[21]), "+f"(d[22]), "+f"(d[23]), "+f"(d[24]), "+f"(d[25]), "+f"(d[26]), "+f"(d[27]), "+f"(d[28]), "+f"(d[29]), "+f"(d[30]), "+f"(d[31]), "+f"(d[32]), "+f"(d[33]), "+f"(d[34]), "+f"(d[35]), "+f"(d[36]), "+f"(d[37]), "+f"(d[38]), "+f"(d[39]), "+f"(d[40]), "+f"(d[41]), "+f"(d[42]), "+f"(d[43]), "+f"(d[44]), "+f"(d[45]), "+f"(d[46]), "+f"(d[47]), "+f"(d[48]), "+f"(d[49]), "+f"(d[50]), "+f"(d[51]), "+f"(d[52]), "+f"(d[53]), "+f"(d[54]), "+f"(d[55]), "+f"(d[56]), "+f"(d[57]), "+f"(d[58]), "+f"(d[59]), "+f"(d[60]), "+f"(d[61]), "+f"(d[62]), "+f"(d[63]), "+f"(d[64]), "+f"(d[65]), "+f"(d[66]), "+f"(d[67]), "+f"(d[68]), "+f"(d[69]), "+f"(d[70]), "+f"(d[71]), "+f"(d[72]), "+f"(d[73]), "+f"(d[74]), "+f"(d[75]), "+f"(d[76]), "+f"(d[77]), "+f"(d[78]), "+f"(d[79]), "+f"(d[80]), "+f"(d[81]), "+f"(d[82]), "+f"(d[83]), "+f"(d[84]), "+f"(d[85]), "+f"(d[86]), "+f"(d[87]), "+f"(d[88]), "+f"(d[89]), "+f"(d[90]), "+f"(d[91]), "+f"(d[92]), "+f"(d[93]), "+f"(d[94]), "+f"(d[95])
    : "l"(da), "l"(db), "r"(sc));
}
__device__ __forceinline__ void wgmma_n128(float (&d)[64], uint64_t da, uint64_t db, int sc) {
  asm volatile("{\n.reg .pred p;\nsetp.ne.b32 p, %66, 0;\n"
    "wgmma.mma_async.sync.aligned.m64n128k16.f32.bf16.bf16 {%0, %1, %2, %3, %4, %5, %6, %7, %8, %9, %10, %11, %12, %13, %14, %15, %16, %17, %18, %19, %20, %21, %22, %23, %24, %25, %26, %27, %28, %29, %30, %31, %32, %33, %34, %35, %36, %37, %38, %39, %40, %41, %42, %43, %44, %45, %46, %47, %48, %49, %50, %51, %52, %53, %54, %55, %56, %57, %58, %59, %60, %61, %62, %63}, %64, %65, p, 1, 1, 0, 1;\n}\n"
    : "+f"(d[0]), "+f"(d[1]), "+f"(d[2]), "+f"(d[3]), "+f"(d[4]), "+f"(d[5]), "+f"(d[6]), "+f"(d[7]), "+f"(d[8]), "+f"(d[9]), "+f"(d[10]), "+f"(d[11]), "+f"(d[12]), "+f"(d[13]), "+f"(d[14]), "+f"(d[15]), "+f"(d[16]), "+f"(d[17]), "+f"(d[18]), "+f"(d[19]), "+f"(d[20]), "+f"(d[21]), "+f"(d[22]), "+f"(d[23]), "+f"(d[24]), "+f"(d[25]), "+f"(d[26]), "+f"(d[27]), "+f"(d[28]), "+f"(d[29]), "+f"(d[30]), "+f"(d[31]), "+f"(d[32]), "+f"(d[33]), "+f"(d[34]), "+f"(d[35]), "+f"(d[36]), "+f"(d[37]), "+f"(d[38]), "+f"(d[39]), "+f"(d[40]), "+f"(d[41]), "+f"(d[42]), "+f"(d[43]), "+f"(d[44]), "+f"(d[45]), "+f"(d[46]), "+f"(d[47]), "+f"(d[48]), "+f"(d[49]), "+f"(d[50]), "+f"(d[51]), "+f"(d[52]), "+f"(d[53]), "+f"(d[54]), "+f"(d[55]), "+f"(d[56]), "+f"(d[57]), "+f"(d[58]), "+f"(d[59]), "+f"(d[60]), "+f"(d[61]), "+f"(d[62]), "+f"(d[63])
    : "l"(da), "l"(db), "r"(sc));
}
__device__ __forceinline__ void wgmma_n64(float (&d)[32], uint64_t da, uint64_t db, int sc) {
  asm volatile("{\n.reg .pred p;\nsetp.ne.b32 p, %34, 0;\n"
    "wgmma.mma_async.sync.aligned.m64n64k16.f32.bf16.bf16 {%0, %1, %2, %3, %4, %5, %6, %7, %8, %9, %10, %11, %12, %13, %14, %15, %16, %17, %18, %19, %20, %21, %22, %23, %24, %25, %26, %27, %28, %29, %30, %31}, %32, %33, p, 1, 1, 0, 1;\n}\n"
    : "+f"(d[0]), "+f"(d[1]), "+f"(d[2]), "+f"(d[3]), "+f"(d[4]), "+f"(d[5]), "+f"(d[6]), "+f"(d[7]), "+f"(d[8]), "+f"(d[9]), "+f"(d[10]), "+f"(d[11]), "+f"(d[12]), "+f"(d[13]), "+f"(d[14]), "+f"(d[15]), "+f"(d[16]), "+f"(d[17]), "+f"(d[18]), "+f"(d[19]), "+f"(d[20]), "+f"(d[21]), "+f"(d[22]), "+f"(d[23]), "+f"(d[24]), "+f"(d[25]), "+f"(d[26]), "+f"(d[27]), "+f"(d[28]), "+f"(d[29]), "+f"(d[30]), "+f"(d[31])
    : "l"(da), "l"(db), "r"(sc));
}
__device__ __forceinline__ void wgmma_n32(float (&d)[16], uint64_t da, uint64_t db, int sc) {
  asm volatile("{\n.reg .pred p;\nsetp.ne.b32 p, %18, 0;\n"
    "wgmma.mma_async.sync.aligned.m64n32k16.f32.bf16.bf16 {%0, %1, %2, %3, %4, %5, %6, %7, %8, %9, %10, %11, %12, %13, %14, %15}, %16, %17, p, 1, 1, 0, 1;\n}\n"
    : "+f"(d[0]), "+f"(d[1]), "+f"(d[2]), "+f"(d[3]), "+f"(d[4]), "+f"(d[5]), "+f"(d[6]), "+f"(d[7]), "+f"(d[8]), "+f"(d[9]), "+f"(d[10]), "+f"(d[11]), "+f"(d[12]), "+f"(d[13]), "+f"(d[14]), "+f"(d[15])
    : "l"(da), "l"(db), "r"(sc));
}

template <int N> struct MMA;
template <> struct MMA<256> { static __device__ __forceinline__ void run(float (&d)[128], uint64_t a, uint64_t b, int s) { wgmma_n256(d, a, b, s); } };
template <> struct MMA<192> { static __device__ __forceinline__ void run(float (&d)[96], uint64_t a, uint64_t b, int s) { wgmma_n192(d, a, b, s); } };
template <> struct MMA<64>  { static __device__ __forceinline__ void run(float (&d)[32], uint64_t a, uint64_t b, int s) { wgmma_n64(d, a, b, s); } };

template <int NS, int SLOTB, class ISSUE, class BG>
__device__ __forceinline__ void mainloop(uint32_t ring, uint32_t fullb, uint32_t emptyb, int& slot, int& cnt, int nk,
                                         int wg, int lane, ISSUE&& issue, BG&& bg) {
  int prev = -1;
  for (int k = 0; k < nk; k++) {
    if (!mbar_test(fullb + slot * 8, (cnt / NS) & 1)) {
      if (prev >= 0) {
        wg_wait<0>();
        if (lane == 0) mbar_arrive(emptyb + prev * 8);
        prev = -1;
      }
      mbar_wait(fullb + slot * 8, (cnt / NS) & 1);
    }
    uint32_t base = ring + slot * SLOTB;
    wg_fence();
    issue(desc_a(base + wg * 8192), desc_b(base + 16384));
    wg_commit();
    wg_wait<1>();
    if (prev >= 0 && lane == 0) mbar_arrive(emptyb + prev * 8);
    bg(k);
    prev = slot;
    cnt++;
    if (++slot == NS) slot = 0;
  }
  wg_wait<0>();
  if (lane == 0) mbar_arrive(emptyb + prev * 8);
}
template <int R> __device__ __forceinline__ void zero_acc(float (&a)[R]) {
#pragma unroll
  for (int i = 0; i < R; i++) a[i] = 0.f;
}
template <int R> __device__ __forceinline__ void pin_acc(float (&a)[R]) {
#pragma unroll
  for (int i = 0; i < R; i++) asm volatile("" : "+f"(a[i])::"memory");
}
template <int N, int NS, int SLOTB, class BG>
__device__ __forceinline__ void tile_loop(float (&acc)[N / 2], uint32_t ring, uint32_t fullb, uint32_t emptyb,
                                          int& slot, int& cnt, int wg, int lane, BG&& bg) {
  zero_acc(acc);
  mainloop<NS, SLOTB>(ring, fullb, emptyb, slot, cnt, 10, wg, lane, [&](uint64_t da, uint64_t db) {
#pragma unroll
    for (int kk = 0; kk < 4; kk++) MMA<N>::run(acc, da + kk * 2, db + kk * 128, 1);
  }, bg);
  pin_acc(acc);
}

template <int N>
__device__ __forceinline__ void dump_tile(float (&acc)[N / 2], uint32_t stg, int wg, int warp, int lane) {
  int row = wg * 64 + warp * 16 + (lane & 7) + ((lane >> 3) & 1) * 8;
  uint32_t rbase = stg + row * 128;
  int csel = lane >> 4;
#pragma unroll
  for (int jb = 0; jb < N / 8; jb += 2) {
    uint32_t r0 = pack_bf16(acc[4 * jb + 0], acc[4 * jb + 1]);
    uint32_t r1 = pack_bf16(acc[4 * jb + 2], acc[4 * jb + 3]);
    uint32_t r2 = pack_bf16(acc[4 * jb + 4], acc[4 * jb + 5]);
    uint32_t r3 = pack_bf16(acc[4 * jb + 6], acc[4 * jb + 7]);
    int cb = jb + csel;
    uint32_t addr = rbase + (cb >> 3) * 16384 + (((cb & 7) ^ (row & 7)) << 4);
    asm volatile("stmatrix.sync.aligned.m8n8.x4.shared.b16 [%0], {%1,%2,%3,%4};" ::"r"(addr), "r"(r0), "r"(r1), "r"(r2), "r"(r3) : "memory");
  }
}

__device__ __forceinline__ float ex2f(float x) { float y; asm("ex2.approx.ftz.f32 %0, %1;" : "=f"(y) : "f"(x)); return y; }
__device__ __forceinline__ float rcpf(float x) { float y; asm("rcp.approx.ftz.f32 %0, %1;" : "=f"(y) : "f"(x)); return y; }

__device__ __forceinline__ float mish_f(float x, float om, float om2) {
  float e = ex2f(x * 1.4426950408889634f);
  float r = rcpf(fmaf(e, e + 2.f, 2.f));
  return x * fmaf(r, om2, om);
}
__device__ __forceinline__ uint32_t mish2(uint32_t v, uint32_t b, float om, float om2) {
  __nv_bfloat162 x2 = __hadd2(*reinterpret_cast<__nv_bfloat162*>(&v), *reinterpret_cast<__nv_bfloat162*>(&b));
  const uint32_t x = *reinterpret_cast<uint32_t*>(&x2);
  return pack_bf16(mish_f(bf_lo(x), om, om2), mish_f(bf_hi(x), om, om2));
}

__device__ __forceinline__ void mma16816(float (&c)[4], uint32_t a0, uint32_t a1, uint32_t a2, uint32_t a3, uint32_t b0, uint32_t b1) {
  asm volatile("mma.sync.aligned.m16n8k16.row.col.f32.bf16.bf16.f32 {%0,%1,%2,%3}, {%4,%5,%6,%7}, {%8,%9}, {%0,%1,%2,%3};"
               : "+f"(c[0]), "+f"(c[1]), "+f"(c[2]), "+f"(c[3]) : "r"(a0), "r"(a1), "r"(a2), "r"(a3), "r"(b0), "r"(b1));
}

__device__ __forceinline__ void ldsm4(uint32_t (&r)[4], uint32_t a) {
  asm volatile("ldmatrix.sync.aligned.m8n8.x4.shared.b16 {%0,%1,%2,%3}, [%4];" : "=r"(r[0]), "=r"(r[1]), "=r"(r[2]), "=r"(r[3]) : "r"(a) : "memory");
}
__device__ __forceinline__ void ldsm4t(uint32_t (&r)[4], uint32_t a) {
  asm volatile("ldmatrix.sync.aligned.m8n8.x4.trans.shared.b16 {%0,%1,%2,%3}, [%4];" : "=r"(r[0]), "=r"(r[1]), "=r"(r[2]), "=r"(r[3]) : "r"(a) : "memory");
}
__device__ __forceinline__ void ldsm2(uint32_t (&r)[2], uint32_t a) {
  asm volatile("ldmatrix.sync.aligned.m8n8.x2.shared.b16 {%0,%1}, [%2];" : "=r"(r[0]), "=r"(r[1]) : "r"(a) : "memory");
}

__device__ __forceinline__ uint4* mish_ptr(uint8_t* stp, int s, int i, int ct) {
  const int row = (ct >> 3) + 64 * (s & 1) + 32 * i;
  return reinterpret_cast<uint4*>(stp + (s >> 1) * 16384 + row * 128 + (((ct & 7) ^ (row & 7)) << 4));
}
__device__ __forceinline__ void mish_slice(uint8_t* stp, const float (&omr)[4], const uint4 bv, const uint4 (&v)[2], int s, int ct) {
#pragma unroll
  for (int i = 0; i < 2; i++) {
    const float om = (s & 1) ? omr[2 + i] : omr[i], om2 = -2.f * om;
    uint4 o;
    o.x = mish2(v[i].x, bv.x, om, om2);
    o.y = mish2(v[i].y, bv.y, om, om2);
    o.z = mish2(v[i].z, bv.z, om, om2);
    o.w = mish2(v[i].w, bv.w, om, om2);
    *mish_ptr(stp, s, i, ct) = o;
  }
}

__device__ __forceinline__ void warp_done(uint32_t bar, int lane) {
  fence_async_smem();
  __syncwarp();
  if (lane == 0) mbar_arrive(bar);
}

__global__ void __cluster_dims__(2, 1, 1) __launch_bounds__(NTHREADS, 1)
fused_kernel(const __grid_constant__ Maps maps, const __nv_bfloat16* __restrict__ b1,
             const __nv_bfloat16* __restrict__ gate_w) {
  extern __shared__ uint8_t smem_raw[];
  const uint32_t ring = (s2u(smem_raw) + 1023) & ~1023u;
  const uint32_t bars = ring + MISC_OFF;
  uint8_t* const sp = smem_raw + (ring - s2u(smem_raw));
  const int tid = threadIdx.x, wgi = tid >> 7, warp = (tid >> 5) & 3, lane = tid & 31;
  const int cta = blockIdx.x;
  const bool regular = cta < NREG_CTAS;
  const int rb = cta & 15, j = cta >> 4;
  const int nw1 = j < 6 ? 4 : (j == 6 ? 3 : 0);
  const int w1_at0 = 4 * j;
  const int q1_at0 = j == 6 ? 0 : 1;
  const int q2_at0 = 5 + 3 * j;
  const int xrb = (cta - NREG_CTAS) * 4;
  const int rank = cta & 1, pr = cta >> 1;
  const int rb2 = pr & 15, nt = pr >> 4;

  if (tid == 0) {
    for (int i = 0; i < 6; i++) { mbar_init(bars + (B_FULL1 + i) * 8, 1); mbar_init(bars + (B_EMPTY1 + i) * 8, regular ? 11 : 8); }
    for (int i = 0; i < 4; i++) { mbar_init(bars + (B_FULL2 + i) * 8, 1); mbar_init(bars + (B_EMPTY2 + i) * 8, 8); }
    mbar_init(bars + B_STGFULL * 8, 1);
    mbar_init(bars + B_STGFREE * 8, regular ? 2 : 1);
    mbar_init(bars + B_GREADY * 8, 3);
    mbar_init(bars + B_ATTFULL * 8, 1);
    mbar_init(bars + B_PEERFREE * 8, 1);
    mbar_init(bars + B_PEERDATA * 8, 1);
    mbar_init(bars + B_HDONE * 8, 8);
    for (int i = 0; i < 3; i++) mbar_init(bars + (B_HD1 + i) * 8, 8);
    mbar_init(bars + B_ODONE * 8, 8);
    mbar_expect(bars + B_PEERDATA * 8, 40960);
    asm volatile("fence.mbarrier_init.release.cluster;" ::: "memory");
  }
  if (tid == 32) {
    const CUtensorMap* mp = &maps.x;
    for (int i = 0; i < 12; i++) asm volatile("prefetch.tensormap [%0];" ::"l"(mp + i) : "memory");
  }
  __syncthreads();
  asm volatile("barrier.cluster.arrive.release.aligned;" ::: "memory");

  if (wgi == 0) {
   asm volatile("setmaxnreg.dec.sync.aligned.u32 104;");
   const uint32_t stg = ring + STG_OFF;
   if (tid < 32) {
    if (tid == 0) {
      if (!regular) {
        int slot = 0;
        for (int i = 0; i < 40; i++) {
          mbar_wait(bars + (B_EMPTY1 + slot) * 8, ((i / 6) & 1) ^ 1);
          uint32_t base = ring + slot * SLOTX, fb = bars + (B_FULL1 + slot) * 8;
          const int t = i / 10, k = i - t * 10;
          mbar_expect(fb, SLOTX);
          tma_load(base, &maps.x, fb, k * 64, (xrb + t) * 128);
          tma_load(base + 16384, &maps.wqkv, fb, 29 * 64, k * 64);
          if (++slot == 6) slot = 0;
        }
      } else {
        for (int k = 0; k < 10; k++) {
          const int slot = k & 3;
          mbar_wait(bars + (B_EMPTY1 + slot) * 8, ((k >> 2) & 1) ^ 1);
          uint32_t base = ring + slot * SLOT1, fb = bars + (B_FULL1 + slot) * 8;
          mbar_expect(fb, SLOT1);
          tma_load(base, &maps.x, fb, k * 64, rb * 128);
          for (int a = 0; a < 4; a++) {
            if (a < nw1) tma_load(base + 16384 + a * 8192, &maps.w1, fb, (w1_at0 + a) * 64, k * 64);
            else tma_load(base + 16384 + a * 8192, &maps.wqkv, fb, (q1_at0 + a - nw1) * 64, k * 64);
          }
        }
        const int nh = rank == 0 ? 14 : 13, h0 = rank == 0 ? 0 : 14, o0 = rank == 0 ? 0 : 5;
        const int c0 = (nt & 1) ? 160 * nt + 32 : 160 * nt;
        const int c2 = (nt & 1) ? 160 * nt - 32 : 160 * nt + 128;
        for (int i = 0; i < 10 + nh + 5; i++) {
          const int slot = (i + 3) & 3;
          if (i < 4) {
            if (i == 0) { mbar_wait(bars + (B_EMPTY1 + 2) * 8, 1); mbar_wait(bars + (B_EMPTY1 + 3) * 8, 1); }
            else if (i == 1) mbar_wait(bars + (B_EMPTY1 + 0) * 8, 0);
            else if (i == 2) mbar_wait(bars + (B_EMPTY1 + 1) * 8, 0);
          } else mbar_wait(bars + (B_EMPTY2 + slot) * 8, ((i >> 2) & 1) ^ 1);
          uint32_t base = ring + slot * SLOT2, fb = bars + (B_FULL2 + slot) * 8;
          if (i < 10) {
            mbar_expect(fb, SLOT2);
            tma_load(base, &maps.x, fb, i * 64, rb * 128);
            for (int a = 0; a < 3; a++) tma_load(base + 16384 + a * 8192, &maps.wqkv, fb, (q2_at0 + a) * 64, i * 64);
          } else {
            const int p = i - 10;
            if (p == 0) { flag_wait(&g_flags[(F_H + rb2) * FSTR], 7); fence_async(); }
            if (p == nh) { flag_wait(&g_flags[(F_O + rb2) * FSTR], 8); fence_async(); }
            mbar_expect(fb, SLOT2);
            const bool hp = p < nh;
            const int kc = (hp ? h0 + p : o0 + p - nh) * 64;
            const CUtensorMap* ma = hp ? &maps.h : &maps.o;
            const CUtensorMap* mb = hp ? &maps.w2 : &maps.wo;
            tma_load(base, ma, fb, kc, rb2 * 128);
            tma_load(base + 16384, mb, fb, c0, kc);
            tma_load(base + 16384 + 8192, mb, fb, c0 + 64, kc);
            tma_load(base + 16384 + 16384, mb, fb, c2, kc);
          }
        }
        finish_reader();
      }
    }
    __syncwarp();
    asm volatile("barrier.cluster.wait.acquire.aligned;" ::: "memory");
   } else if (!regular) {
    asm volatile("barrier.cluster.wait.acquire.aligned;" ::: "memory");
    if (tid == 32) {
      for (int t = 0; t < 4; t++) {
        mbar_wait(bars + B_STGFULL * 8, t & 1);
        tma_store(&maps.qkv_st, stg, 29 * 64, (xrb + t) * 128);
        bulk_commit_wait();
        mbar_arrive(bars + B_STGFREE * 8);
        flag_add(&g_flags[(F_QKV + xrb + t) * FSTR]);
      }
    }
   } else {
    const int t = tid - 32;
    float* const sGp = reinterpret_cast<float*>(sp + SG_OFF);
    {
      const int ch = t & 7, r0 = t >> 3;
      float dot[11];
#pragma unroll
      for (int i = 0; i < 11; i++) dot[i] = 0.f;
      for (int k = 0; k < 10; k++) {
        uint4 w = __ldg(reinterpret_cast<const uint4*>(gate_w + k * 64 + ch * 8));
        mbar_wait(bars + (B_FULL1 + (k & 3)) * 8, (k >> 2) & 1);
        const uint8_t* abase = sp + (k & 3) * SLOT1;
        uint4 a[11];
#pragma unroll
        for (int i = 0; i < 11; i++) {
          int row = min(r0 + 12 * i, 127);
          a[i] = *reinterpret_cast<const uint4*>(abase + row * 128 + ((ch ^ (row & 7)) << 4));
        }
#pragma unroll
        for (int i = 0; i < 11; i++)
          dot[i] += bf_lo(a[i].x) * bf_lo(w.x) + bf_hi(a[i].x) * bf_hi(w.x) + bf_lo(a[i].y) * bf_lo(w.y) + bf_hi(a[i].y) * bf_hi(w.y)
                  + bf_lo(a[i].z) * bf_lo(w.z) + bf_hi(a[i].z) * bf_hi(w.z) + bf_lo(a[i].w) * bf_lo(w.w) + bf_hi(a[i].w) * bf_hi(w.w);
#pragma unroll
        for (int i = 0; i < 11; i++) asm volatile("" : "+f"(dot[i])::"memory");
        __syncwarp();
        if (lane == 0) mbar_arrive(bars + (B_EMPTY1 + (k & 3)) * 8);
      }
#pragma unroll
      for (int i = 0; i < 11; i++) {
        float d = dot[i];
        d += __shfl_xor_sync(0xffffffffu, d, 1); d += __shfl_xor_sync(0xffffffffu, d, 2); d += __shfl_xor_sync(0xffffffffu, d, 4);
        int row = r0 + 12 * i;
        if (ch == 0 && row < 128) sGp[row] = rcpf(1.f + ex2f(-1.4426950408889634f * d));
      }
      __syncwarp();
      if (lane == 0) mbar_arrive(bars + B_GREADY * 8);
    }
    asm volatile("barrier.cluster.wait.acquire.aligned;" ::: "memory");
    if (t == 32) {
      for (int a = 0; a < nw1; a++) {
        mbar_wait(bars + (a == 0 ? B_HDONE : B_HD1 + a - 1) * 8, 0);
        tma_store(&maps.h, stg + a * 16384, (w1_at0 + a) * 64, rb * 128);
      }
      if (nw1 > 0) { bulk_commit_wait(); flag_add(&g_flags[(F_H + rb) * FSTR]); }
      mbar_arrive(bars + B_STGFREE * 8);
      mbar_wait(bars + B_ODONE * 8, 0);
      tma_store3(&maps.o_st, stg, 80 * j, rb * 64);
      bulk_commit_wait();
      flag_add(&g_flags[(F_O + rb) * FSTR]);
      mbar_arrive_cl(mapa(bars + B_PEERFREE * 8, rank ^ 1));
    } else if (t == 0) {
      mbar_wait(bars + B_STGFULL * 8, 0);
      if (nw1 < 4) {
        for (int a = nw1; a < 4; a++) tma_store(&maps.qkv_st, stg + a * 16384, (q1_at0 + a - nw1) * 64, rb * 128);
        bulk_commit_wait();
        flag_add(&g_flags[(F_QKV + rb) * FSTR]);
      }
      mbar_arrive(bars + B_STGFREE * 8);
      mbar_wait(bars + B_STGFULL * 8, 1);
      for (int a = 0; a < 3; a++) tma_store(&maps.qkv_st, stg + a * 16384, (q2_at0 + a) * 64, rb * 128);
      bulk_commit_wait();
      flag_add(&g_flags[(F_QKV + rb) * FSTR]);
      flag_wait(&g_flags[(F_QKV + rb) * FSTR], 11);
      if (rb > 0) flag_wait(&g_flags[(F_QKV + rb - 1) * FSTR], 11);
      fence_async();
      uint32_t fb = bars + B_ATTFULL * 8;
      mbar_expect(fb, 128 * 160 + 2 * 142 * 160);
      tma_load3(stg, &maps.qkv_ldq, fb, 80 * j, rb * 64);
      tma_load3(stg + ATT_K_OFF, &maps.qkv_ldkv, fb, 640 + 80 * j, rb * 64 - 7);
      tma_load3(stg + ATT_V_OFF, &maps.qkv_ldkv, fb, 1280 + 80 * j, rb * 64 - 7);
      finish_reader();
    }
   }
  } else {
    asm volatile("setmaxnreg.inc.sync.aligned.u32 200;");
    const int wg = wgi - 1;
    int slot = 0, cnt = 0;
    const int ct = tid - 128;
    uint8_t* const stp = sp + STG_OFF;
    const float* const sGp = reinterpret_cast<const float*>(sp + SG_OFF);
    auto nobg = [](int) {};
    if (!regular) {
      asm volatile("barrier.cluster.wait.acquire.aligned;" ::: "memory");
      for (int tl = 0; tl < 4; tl++) {
        float acc[32];
        tile_loop<64, 6, SLOTX>(acc, ring, bars + B_FULL1 * 8, bars + B_EMPTY1 * 8, slot, cnt, wg, lane, nobg);
        if (tl > 0) mbar_wait(bars + B_STGFREE * 8, (tl - 1) & 1);
        dump_tile<64>(acc, ring + STG_OFF, wg, warp, lane);
        fence_async_smem();
        named_bar(2, 256);
        if (tid == 128) mbar_arrive(bars + B_STGFULL * 8);
      }
    } else {
      uint4 bv[4];
#pragma unroll
      for (int a = 0; a < 4; a++) bv[a] = __ldg(reinterpret_cast<const uint4*>(b1 + min(w1_at0 + a, 26) * 64 + (ct & 7) * 8));
      {
        float acc[128];
        tile_loop<256, 4, SLOT1>(acc, ring, bars + B_FULL1 * 8, bars + B_EMPTY1 * 8, slot, cnt, wg, lane, nobg);
        named_bar(2, 256);
        dump_tile<256>(acc, ring + STG_OFF, wg, warp, lane);
        fence_async_smem();
        named_bar(2, 256);
      }
      if (tid == 128) mbar_arrive(bars + B_STGFULL * 8);
      asm volatile("barrier.cluster.wait.acquire.aligned;" ::: "memory");
      slot = 3; cnt = 0;
      {
        float acc[96];
        float omr[4];
        uint4 vn[2];
        tile_loop<192, 4, SLOT2>(acc, ring, bars + B_FULL2 * 8, bars + B_EMPTY2 * 8, slot, cnt, wg, lane, [&](int k1) {
          const int k = k1 - 1;
          if (k == 0) {
            mbar_wait(bars + B_GREADY * 8, 0);
#pragma unroll
            for (int i = 0; i < 4; i++) omr[i] = 1.f - sGp[(ct >> 3) + 32 * i];
            vn[0] = *mish_ptr(stp, 0, 0, ct); vn[1] = *mish_ptr(stp, 0, 1, ct);
          }
          if (k >= 0 && k < nw1) {
            const uint4 b = k == 0 ? bv[0] : k == 1 ? bv[1] : k == 2 ? bv[2] : bv[3];
#pragma unroll 1
            for (int sl = 2 * k; sl < 2 * k + 2; sl++) {
              const uint4 v[2] = {vn[0], vn[1]};
              if (sl + 1 < 2 * nw1) { vn[0] = *mish_ptr(stp, sl + 1, 0, ct); vn[1] = *mish_ptr(stp, sl + 1, 1, ct); }
              mish_slice(stp, omr, b, v, sl, ct);
            }
            warp_done(bars + (k == 0 ? B_HDONE : B_HD1 + k - 1) * 8, lane);
          }
        });
        mbar_wait(bars + B_STGFREE * 8, 0);
        named_bar(2, 256);
        dump_tile<192>(acc, ring + STG_OFF, wg, warp, lane);
        fence_async_smem();
        named_bar(2, 256);
      }
      if (tid == 128) mbar_arrive(bars + B_STGFULL * 8);

      const int g8 = lane >> 2, c4 = lane & 3;
      const int par = warp & 1, P0 = ((wg * 4 + warp) >> 1) * 16;
      const uint32_t stq = ring + STG_OFF + par * (64 * 160);
      const uint32_t stk = ring + STG_OFF + ATT_K_OFF + par * (71 * 160);
      const uint32_t stv = ring + STG_OFF + ATT_V_OFF + par * (71 * 160);
      int ast = 0;
      auto att_step = [&]() {
        const bool oddh = (ast & 1) != 0;
        const int hoffb = ast * 40 - (oddh ? 8 : 0);
        uint32_t qa[4], qb[2];
        {
          const uint32_t qrow = stq + (P0 + (lane & 7) + ((lane >> 3) & 1) * 8) * 160 + hoffb;
          ldsm4(qa, qrow + (lane >> 4) * 16);
          ldsm2(qb, qrow + 32);
          if (oddh) { if (c4 < 2) { qa[0] = 0u; qa[1] = 0u; } }
          else if (c4 >= 2) { qb[0] = 0u; qb[1] = 0u; }
        }
        const int chunk = min(lane >> 3, 2);
        float sfr[3][4];
#pragma unroll
        for (int n = 0; n < 3; n++) {
          uint32_t kb[4];
          ldsm4(kb, stk + min(P0 + 8 * n + (lane & 7), 70) * 160 + hoffb + chunk * 16);
          sfr[n][0] = sfr[n][1] = sfr[n][2] = sfr[n][3] = 0.f;
          mma16816(sfr[n], qa[0], qa[1], qa[2], qa[3], kb[0], kb[1]);
          mma16816(sfr[n], qb[0], qb[1], 0u, 0u, kb[2], 0u);
        }
        uint32_t vb[3][4];
#pragma unroll
        for (int d = 0; d < 3; d++) ldsm4t(vb[d], stv + min(P0 + 8 * chunk + (lane & 7), 70) * 160 + hoffb + d * 16);
        const float sc = 0.22360679774997896f * 1.4426950408889634f;
        const int tmin = 7 - (rb * 64 + P0);
        float mx0 = -3.0e38f, mx1 = -3.0e38f;
#pragma unroll
        for (int n = 0; n < 3; n++) {
#pragma unroll
          for (int e = 0; e < 2; e++) {
            const int t = 8 * n + 2 * c4 + e;
            sfr[n][e] = (t >= g8 && t <= g8 + 7 && t >= tmin) ? sfr[n][e] * sc : -3.0e38f;
            sfr[n][2 + e] = (t >= g8 + 8 && t <= g8 + 15 && t >= tmin) ? sfr[n][2 + e] * sc : -3.0e38f;
            mx0 = fmaxf(mx0, sfr[n][e]); mx1 = fmaxf(mx1, sfr[n][2 + e]);
          }
        }
        mx0 = fmaxf(mx0, __shfl_xor_sync(0xffffffffu, mx0, 1)); mx1 = fmaxf(mx1, __shfl_xor_sync(0xffffffffu, mx1, 1));
        mx0 = fmaxf(mx0, __shfl_xor_sync(0xffffffffu, mx0, 2)); mx1 = fmaxf(mx1, __shfl_xor_sync(0xffffffffu, mx1, 2));
        float s0 = 0.f, s1 = 0.f;
#pragma unroll
        for (int n = 0; n < 3; n++) {
#pragma unroll
          for (int e = 0; e < 2; e++) {
            sfr[n][e] = ex2f(sfr[n][e] - mx0); sfr[n][2 + e] = ex2f(sfr[n][2 + e] - mx1);
            s0 += sfr[n][e]; s1 += sfr[n][2 + e];
          }
        }
        s0 += __shfl_xor_sync(0xffffffffu, s0, 1); s1 += __shfl_xor_sync(0xffffffffu, s1, 1);
        s0 += __shfl_xor_sync(0xffffffffu, s0, 2); s1 += __shfl_xor_sync(0xffffffffu, s1, 2);
        const uint32_t p0 = pack_bf16(sfr[0][0], sfr[0][1]), p1 = pack_bf16(sfr[0][2], sfr[0][3]);
        const uint32_t p2 = pack_bf16(sfr[1][0], sfr[1][1]), p3 = pack_bf16(sfr[1][2], sfr[1][3]);
        const uint32_t p4 = pack_bf16(sfr[2][0], sfr[2][1]), p5 = pack_bf16(sfr[2][2], sfr[2][3]);
        const float f0 = sGp[2 * (P0 + g8) + par] * rcpf(s0), f1 = sGp[2 * (P0 + g8 + 8) + par] * rcpf(s1);
        float ofr[3][4];
#pragma unroll
        for (int d = 0; d < 3; d++) {
          ofr[d][0] = ofr[d][1] = ofr[d][2] = ofr[d][3] = 0.f;
          mma16816(ofr[d], p0, p1, p2, p3, vb[d][0], vb[d][1]);
          mma16816(ofr[d], p4, p5, 0u, 0u, vb[d][2], 0u);
        }
        __syncwarp();
        uint8_t* op = stp + par * (64 * 160) + (P0 + g8) * 160 + hoffb + c4 * 4;
#pragma unroll
        for (int d = 0; d < 3; d++) {
          const bool ok = oddh ? (d > 0 || c4 >= 2) : (d < 2 || c4 < 2);
          if (ok) {
            *reinterpret_cast<uint32_t*>(op + d * 16) = pack_bf16(ofr[d][0] * f0, ofr[d][1] * f0);
            *reinterpret_cast<uint32_t*>(op + 8 * 160 + d * 16) = pack_bf16(ofr[d][2] * f1, ofr[d][3] * f1);
          }
        }
        if (ast == 3) {
          warp_done(bars + B_ODONE * 8, lane);
        }
        ast++;
      };
      const int nh = rank == 0 ? 14 : 13;
      float accA[64], accB[16];
      zero_acc(accA); zero_acc(accB);
      const uint64_t hoff = 1024 + ((nt & 1) ? 4 : 0);
      mainloop<4, SLOT2>(ring, bars + B_FULL2 * 8, bars + B_EMPTY2 * 8, slot, cnt, nh + 5, wg, lane, [&](uint64_t da, uint64_t db) {
#pragma unroll
        for (int kk = 0; kk < 4; kk++) {
          wgmma_n128(accA, da + kk * 2, db + kk * 128, 1);
          wgmma_n32(accB, da + kk * 2, db + hoff + kk * 128, 1);
        }
      }, [&](int k) {
        if (k == K_ATT) {
          mbar_wait(bars + B_ATTFULL * 8, 0);
          wg_wait<0>();
#pragma unroll 2
          for (int hh = 0; hh < 4; hh++) att_step();
        }
      });
      pin_acc(accA); pin_acc(accB);
      float acc[80];
#pragma unroll
      for (int i = 0; i < 64; i++) acc[i] = accA[i];
#pragma unroll
      for (int i = 0; i < 16; i++) acc[64 + i] = accB[i];
      const uint32_t peer = rank ^ 1;
      mbar_wait_cl(bars + B_PEERFREE * 8, 0);
      const uint32_t rdst = mapa(ring + STG_OFF + ATT_K_OFF + ct * 16, peer);
      const uint32_t rbar = mapa(bars + B_PEERDATA * 8, peer);
      const bool odd = (nt & 1) != 0;
      float keep[40], snd[40];
#pragma unroll
      for (int i = 0; i < 10; i++) {
        const int be0 = i, be1 = 10 + i;
        const int bo0 = i < 4 ? 16 + i : i - 4, bo1 = 6 + i;
#pragma unroll
        for (int e = 0; e < 4; e++) {
          const float r0 = odd ? acc[4 * bo0 + e] : acc[4 * be0 + e];
          const float r1 = odd ? acc[4 * bo1 + e] : acc[4 * be1 + e];
          keep[4 * i + e] = rank == 0 ? r0 : r1;
          snd[4 * i + e] = rank == 0 ? r1 : r0;
        }
      }
#pragma unroll
      for (int i = 0; i < 10; i++)
        asm volatile("st.async.shared::cluster.mbarrier::complete_tx::bytes.v4.f32 [%0], {%1,%2,%3,%4}, [%5];"
                     ::"r"(rdst + i * 4096), "f"(snd[4 * i]), "f"(snd[4 * i + 1]), "f"(snd[4 * i + 2]), "f"(snd[4 * i + 3]), "r"(rbar) : "memory");
      mbar_wait_cl(bars + B_PEERDATA * 8, 0);
      uint8_t* orow = sp + (wg * 64 + warp * 16 + (lane >> 2)) * 160 + (lane & 3) * 4;
#pragma unroll
      for (int i = 0; i < 10; i++) {
        const float4 v = *reinterpret_cast<const float4*>(stp + ATT_K_OFF + ct * 16 + i * 4096);
        *reinterpret_cast<uint32_t*>(orow + i * 16) = pack_bf16(v.x + keep[4 * i], v.y + keep[4 * i + 1]);
        *reinterpret_cast<uint32_t*>(orow + 8 * 160 + i * 16) = pack_bf16(v.z + keep[4 * i + 2], v.w + keep[4 * i + 3]);
      }
      fence_async_smem();
      named_bar(2, 256);
      if (tid == 128) {
        tma_store(&maps.out_st, ring, 160 * nt + 80 * rank, rb2 * 128);
        asm volatile("cp.async.bulk.commit_group;" ::: "memory");
        asm volatile("cp.async.bulk.wait_group.read 0;" ::: "memory");
      }
    }
  }
}

typedef CUresult (*EncFn)(CUtensorMap*, CUtensorMapDataType, cuuint32_t, void*, const cuuint64_t*, const cuuint64_t*,
                          const cuuint32_t*, const cuuint32_t*, CUtensorMapInterleave, CUtensorMapSwizzle,
                          CUtensorMapL2promotion, CUtensorMapFloatOOBfill);

void make_map(EncFn enc, CUtensorMap* m, const void* p, int cols, int rows, int bc, int br, bool swz) {
  cuuint64_t d[2] = {(cuuint64_t)cols, (cuuint64_t)rows};
  cuuint64_t s[1] = {(cuuint64_t)cols * 2};
  cuuint32_t b[2] = {(cuuint32_t)bc, (cuuint32_t)br};
  cuuint32_t e[2] = {1, 1};
  enc(m, CU_TENSOR_MAP_DATA_TYPE_BFLOAT16, 2, const_cast<void*>(p), d, s, b, e, CU_TENSOR_MAP_INTERLEAVE_NONE,
      swz ? CU_TENSOR_MAP_SWIZZLE_128B : CU_TENSOR_MAP_SWIZZLE_NONE, CU_TENSOR_MAP_L2_PROMOTION_L2_128B,
      CU_TENSOR_MAP_FLOAT_OOB_FILL_NONE);
}

void make_map3(EncFn enc, CUtensorMap* m, const void* p, int cols, int rows, int bc, int bpairs) {
  cuuint64_t d[3] = {(cuuint64_t)cols, (cuuint64_t)rows / 2, 2};
  cuuint64_t s[2] = {(cuuint64_t)cols * 4, (cuuint64_t)cols * 2};
  cuuint32_t b[3] = {(cuuint32_t)bc, (cuuint32_t)bpairs, 2};
  cuuint32_t e[3] = {1, 1, 1};
  enc(m, CU_TENSOR_MAP_DATA_TYPE_BFLOAT16, 3, const_cast<void*>(p), d, s, b, e, CU_TENSOR_MAP_INTERLEAVE_NONE,
      CU_TENSOR_MAP_SWIZZLE_NONE, CU_TENSOR_MAP_L2_PROMOTION_L2_128B, CU_TENSOR_MAP_FLOAT_OOB_FILL_NONE);
}

}

extern "C" void kernel_launch(void* const* d_in, const int* in_sizes, int n_in, void* d_out, int out_size) {
  (void)in_sizes; (void)n_in; (void)out_size;
  static Maps maps;
  static const void* seen[9] = {nullptr};
  bool same = seen[8] == d_out;
  for (int i = 0; i < 8; i++) same = same && seen[i] == d_in[i];
  if (!same) {
    for (int i = 0; i < 8; i++) seen[i] = d_in[i];
    seen[8] = d_out;
    EncFn enc = nullptr;
    cudaDriverEntryPointQueryResult q;
    cudaGetDriverEntryPoint("cuTensorMapEncodeTiled", (void**)&enc, cudaEnableDefault, &q);
    void *ph, *po, *pq;
    cudaGetSymbolAddress(&ph, g_h);
    cudaGetSymbolAddress(&po, g_o);
    cudaGetSymbolAddress(&pq, g_qkv);
    make_map(enc, &maps.x, d_in[0], DM, SEQ, 64, 128, true);
    make_map(enc, &maps.wqkv, d_in[1], QKVN, DM, 64, 64, true);
    make_map(enc, &maps.wo, d_in[2], DM, DM, 64, 64, true);
    make_map(enc, &maps.w1, d_in[4], FF, DM, 64, 64, true);
    make_map(enc, &maps.w2, d_in[6], DM, FF, 64, 64, true);
    make_map(enc, &maps.h, ph, FF, SEQ, 64, 128, true);
    make_map(enc, &maps.o, po, DM, SEQ, 64, 128, true);
    make_map(enc, &maps.qkv_st, pq, QKVN, SEQ, 64, 128, true);
    make_map3(enc, &maps.qkv_ldq, pq, QKVN, SEQ, 80, 64);
    make_map3(enc, &maps.qkv_ldkv, pq, QKVN, SEQ, 80, 71);
    make_map3(enc, &maps.o_st, po, DM, SEQ, 80, 64);
    make_map(enc, &maps.out_st, d_out, DM, SEQ, 80, 128, false);
    cudaFuncSetAttribute(fused_kernel, cudaFuncAttributeMaxDynamicSharedMemorySize, SMEM_ALLOC);
  }
  fused_kernel<<<NCTAS, NTHREADS, SMEM_ALLOC>>>(maps, (const __nv_bfloat16*)d_in[5], (const __nv_bfloat16*)d_in[7]);
}
```
